```python
import torch

def _softmax(x, axis=-1):
    return torch.softmax(x, dim=axis)
def _gelu(x):
    return torch.nn.functional.gelu(x, approximate="tanh")
def _silu(x):
    return torch.nn.functional.silu(x)
def _sigmoid(x):
    return torch.sigmoid(x)
def _layernorm(x, axis=-1, eps=1e-5):
    m = x.mean(dim=axis, keepdim=True)
    v = x.var(dim=axis, keepdim=True, unbiased=False)
    return (x - m) / torch.sqrt(v + eps)
def _scatter_add(tgt, idx, src, axis=0):
    return tgt.clone().index_add_(axis, idx, src)
def _segment_sum(src, seg, n):
    out = torch.zeros((n,) + src.shape[1:], dtype=src.dtype)
    return out.index_add_(0, seg, src)
def _pad(x, pw):
    flat = tuple(v for pair in reversed(pw) for v in pair)
    return torch.nn.functional.pad(x, flat)

kernel_name = 'parallel_sum__compressed_kv_cla__moe_arch_mod__prompt'

def setup_inputs():

    _w = (lambda a: (lambda t: t.to(torch.bfloat16) if t.is_floating_point() else t)(torch.as_tensor(a)))
    def _A_setup():
        B, H, Sq, Sk, D, M = 1, 32, 2048, 2048, 128, 512
        Dc = 4 * D
        return {
            "x": _w((lambda *s: torch.randn(*s, dtype=torch.bfloat16) * 0.05)(B, Sq, M)),
            "c_kv": _w((lambda *s: torch.randn(*s, dtype=torch.bfloat16) * 1.6)(B, Sk, Dc)),
            "w_q": _w((lambda *s: torch.randn(*s, dtype=torch.bfloat16) * 0.8)(M, H, D) * (M ** -0.5)),
            "w_uk": _w((lambda *s: torch.randn(*s, dtype=torch.bfloat16) * 0.8)(Dc, H, D) * (Dc ** -0.5)),
            "w_uv": _w((lambda *s: torch.randn(*s, dtype=torch.bfloat16) * 1.6)(Dc, H, D) * (Dc ** -0.5)),
            "w_o": _w((lambda *s: torch.randn(*s, dtype=torch.bfloat16) * 1.6)(H, D, M) * ((H * D) ** -0.5)),
        }
    _A_in = _A_setup()

    def _B_setup():
        B, S, D, F, C = 1, 2048, 512, 1792, 1
        return {
            "x": _w((lambda *s: torch.randn(*s, dtype=torch.bfloat16) * 0.05)(B, S, D)),
            "w_r": _w((lambda *s: torch.randn(*s, dtype=torch.bfloat16) * 0.05)(D)),
            "w_gate": _w((lambda *s: torch.randn(*s, dtype=torch.bfloat16) * 0.05)(D, F)),
            "w_up": _w((lambda *s: torch.randn(*s, dtype=torch.bfloat16) * 0.05)(D, F)),
            "w_down": _w((lambda *s: torch.randn(*s, dtype=torch.bfloat16) * 0.05)(F, D)),
        }
    _B_in = _B_setup()

    return {
        "A_x": _A_in["x"],
        "A_c_kv": _A_in["c_kv"],
        "A_w_q": _A_in["w_q"],
        "A_w_uk": _A_in["w_uk"],
        "A_w_uv": _A_in["w_uv"],
        "A_w_o": _A_in["w_o"],
        "B_x": _B_in["x"],
        "B_w_r": _B_in["w_r"],
        "B_w_gate": _B_in["w_gate"],
        "B_w_up": _B_in["w_up"],
        "B_w_down": _B_in["w_down"],
    }

def reference(A_x, A_c_kv, A_w_q, A_w_uk, A_w_uv, A_w_o, B_x, B_w_r, B_w_gate, B_w_up, B_w_down):
    def _A_ref(x, c_kv, w_q, w_uk, w_uv, w_o):
        B, Sq, M = x.shape[0], x.shape[1], x.shape[2]
        Sk = c_kv.shape[1]
        H, D = w_q.shape[1], w_q.shape[2]
        q = torch.einsum("bqm,mhd->bhqd", x, w_q)
        k = torch.einsum("bkc,chd->bhkd", c_kv, w_uk)
        v = torch.einsum("bkc,chd->bhkd", c_kv, w_uv)
        scores = torch.einsum("bhqd,bhkd->bhqk", q, k) * (D ** -0.5)
        off = Sk - Sq
        qi = torch.arange(Sq)[:, None]
        kj = torch.arange(Sk)[None, :]
        cmask = kj <= (qi + off)
        scores = torch.where(cmask[None, None], scores, -1e9)
        p = _softmax(scores, axis=-1)
        ctx = torch.einsum("bhqk,bhkd->bhqd", p, v)
        return torch.einsum("bhqd,hdm->bqm", ctx, w_o)

    def _B_ref(x, w_r, w_gate, w_up, w_down):
        B, S, D = x.shape
        C = 1
        r = x @ w_r
        idx = torch.argsort(-r, axis=-1)[:, :C]
        idx_e = (lambda x, n, axis: torch.repeat_interleave(x, n, dim=axis))(idx.reshape(B, C, 1), D, axis=2)
        x_sel = (lambda x, i, axis: torch.take_along_dim(x, i, dim=axis))(x, idx_e, axis=1)
        g = _silu(x_sel @ w_gate)
        u = x_sel @ w_up
        y = (g * u) @ w_down
        r_sel = _sigmoid((lambda x, i, axis: torch.take_along_dim(x, i, dim=axis))(r, idx, axis=1))
        y = y * r_sel.reshape(B, C, 1)
        b_off = (torch.arange(B) * S).reshape(B, 1)
        flat_idx = (idx + b_off).reshape(B * C)
        zero = (x * 0.0).reshape(B * S, D)
        upd = _scatter_add(zero, flat_idx, y.reshape(B * C, D), axis=0)
        return x + upd.reshape(B, S, D)

    x = A_x
    xn = _layernorm(x, axis=-1)
    return x + _A_ref(xn, A_c_kv, A_w_q, A_w_uk, A_w_uv, A_w_o) + _B_ref(xn, B_w_r, B_w_gate, B_w_up, B_w_down)
```

```cpp
#include <cuda_runtime.h>
#include <cuda_bf16.h>
#include <cuda.h>
#include <stdint.h>
#include <string.h>

namespace {

constexpr int SEQ = 2048, DM = 512, NH = 32, FF = 1792;
constexpr int NPAIR = 66, NCTA = 132;
constexpr int MAXIT = 8;
constexpr int NST = 6;
constexpr uint32_t STAGE = 32768;
constexpr uint32_t SM_STG = NST * STAGE;
constexpr uint32_t SM_BAR = SM_STG + 32768;
constexpr uint32_t SMEM_BYTES = SM_BAR + 256 + 1024;
constexpr uint32_t B_FULL = 0, B_EMPTY = 64, B_STFREE = 128, B_DONE = 144;

enum { IT_END = 0, IT_KV = 1, IT_ATT = 2, IT_OP = 3, IT_MOE = 4 };

struct alignas(64) Params {
  CUtensorMap tm_ckv, tm_wq, tm_wuk, tm_wuv, tm_wo;
  const __nv_bfloat16 *x, *w_r, *w_gate, *w_up, *w_down;
  __nv_bfloat16* out;
  uint32_t items[NPAIR][MAXIT];
  uint8_t korder[8][32];
};

struct Flags {
  unsigned long long key; unsigned pad0[30];
  unsigned ln_done; unsigned pad1[31];
  unsigned moe_done; unsigned exit_cnt; unsigned pad2[30];
  unsigned kv_done[64];
  unsigned ctx_done[256];
  unsigned ex_done[256];
};

__device__ Flags g_flags;
__device__ __align__(1024) unsigned char g_kv[(size_t)NH * 2 * 16 * 32768];
__device__ __align__(1024) unsigned char g_xn[(size_t)32 * 8 * 8192];
__device__ __align__(1024) unsigned char g_ctx[(size_t)32 * NH * 16384];
__device__ __align__(1024) float4 g_exch[(size_t)16 * 4 * 3 * 4 * 1024];
__device__ float g_ypart[4 * DM];

__device__ __forceinline__ uint32_t smem_u32(const void* p) { return (uint32_t)__cvta_generic_to_shared(p); }
__device__ __forceinline__ void mbar_init(uint32_t bar, int cnt) {
  asm volatile("mbarrier.init.shared::cta.b64 [%0], %1;" ::"r"(bar), "r"(cnt) : "memory");
}
__device__ __forceinline__ void mbar_expect_tx(uint32_t bar, uint32_t bytes) {
  asm volatile("mbarrier.arrive.expect_tx.shared::cta.b64 _, [%0], %1;" ::"r"(bar), "r"(bytes) : "memory");
}
__device__ __forceinline__ void mbar_arrive(uint32_t bar) {
  asm volatile("mbarrier.arrive.shared::cta.b64 _, [%0];" ::"r"(bar) : "memory");
}
__device__ __forceinline__ void mbar_arrive_cta(uint32_t bar, uint32_t cta) {
  asm volatile("{\n.reg .b32 r;\nmapa.shared::cluster.u32 r, %0, %1;\nmbarrier.arrive.shared::cluster.b64 _, [r];\n}\n" ::"r"(bar), "r"(cta) : "memory");
}
__device__ __forceinline__ bool mbar_try(uint32_t bar, uint32_t parity) {
  uint32_t ok;
  asm volatile("{\n.reg .pred p;\nmbarrier.try_wait.parity.shared::cta.b64 p, [%1], %2;\nselp.u32 %0, 1, 0, p;\n}\n"
               : "=r"(ok) : "r"(bar), "r"(parity) : "memory");
  return ok != 0;
}
__device__ __forceinline__ uint32_t clk32() { uint32_t c; asm volatile("mov.u32 %0, %%clock;" : "=r"(c)); return c; }
constexpr uint32_t TIMEOUT_CLKS = 1u << 30;
__device__ __forceinline__ void mbar_wait(uint32_t bar, uint32_t parity) {
  asm volatile("{\n.reg .pred p;\nWAIT_LOOP:\nmbarrier.try_wait.parity.shared::cta.b64 p, [%0], %1;\n@p bra WAIT_DONE;\nbra WAIT_LOOP;\nWAIT_DONE:\n}\n"
               ::"r"(bar), "r"(parity) : "memory");
}
__device__ __forceinline__ unsigned ld_acquire(const unsigned* p) {
  unsigned v; asm volatile("ld.acquire.gpu.global.u32 %0, [%1];" : "=r"(v) : "l"(p) : "memory"); return v;
}
__device__ __forceinline__ void red_release(unsigned* p, unsigned v) {
  asm volatile("red.release.gpu.global.add.u32 [%0], %1;" ::"l"(p), "r"(v) : "memory");
}
__device__ __forceinline__ void flag_wait(const unsigned* p, unsigned target) {
  while (ld_acquire(p) < target) { __nanosleep(40); }
}
__device__ __forceinline__ void fence_async_all() { asm volatile("fence.proxy.async;" ::: "memory"); }
__device__ __forceinline__ void fence_async_smem() { asm volatile("fence.proxy.async.shared::cta;" ::: "memory"); }
__device__ __forceinline__ void bar_sync(int id, int n) { asm volatile("bar.sync %0, %1;" ::"r"(id), "r"(n) : "memory"); }
__device__ __forceinline__ void bar_arrive(int id, int n) { asm volatile("bar.arrive %0, %1;" ::"r"(id), "r"(n) : "memory"); }

__device__ __forceinline__ void bulk_load(uint32_t dst, const void* src, uint32_t bytes, uint32_t bar) {
  asm volatile("cp.async.bulk.shared::cluster.global.mbarrier::complete_tx::bytes [%0], [%1], %2, [%3];"
               ::"r"(dst), "l"(src), "r"(bytes), "r"(bar) : "memory");
}
__device__ __forceinline__ void bulk_load_mc(uint32_t dst, const void* src, uint32_t bytes, uint32_t bar) {
  asm volatile("cp.async.bulk.shared::cluster.global.mbarrier::complete_tx::bytes.multicast::cluster [%0], [%1], %2, [%3], %4;"
               ::"r"(dst), "l"(src), "r"(bytes), "r"(bar), "h"((uint16_t)3) : "memory");
}
__device__ __forceinline__ void tma_load(uint32_t dst, const CUtensorMap* tm, int c0, int c1, uint32_t bar) {
  asm volatile("cp.async.bulk.tensor.2d.shared::cluster.global.mbarrier::complete_tx::bytes [%0], [%1, {%3, %4}], [%2];"
               ::"r"(dst), "l"(tm), "r"(bar), "r"(c0), "r"(c1) : "memory");
}
__device__ __forceinline__ void tma_load_mc(uint32_t dst, const CUtensorMap* tm, int c0, int c1, uint32_t bar) {
  asm volatile("cp.async.bulk.tensor.2d.shared::cluster.global.mbarrier::complete_tx::bytes.multicast::cluster [%0], [%1, {%3, %4}], [%2], %5;"
               ::"r"(dst), "l"(tm), "r"(bar), "r"(c0), "r"(c1), "h"((uint16_t)3) : "memory");
}
__device__ __forceinline__ void bulk_store(void* dst, uint32_t src, uint32_t bytes) {
  asm volatile("cp.async.bulk.global.shared::cta.bulk_group [%0], [%1], %2;" ::"l"(dst), "r"(src), "r"(bytes) : "memory");
}
__device__ __forceinline__ void bulk_commit() { asm volatile("cp.async.bulk.commit_group;" ::: "memory"); }
__device__ __forceinline__ void bulk_wait_read0() { asm volatile("cp.async.bulk.wait_group.read 0;" ::: "memory"); }
__device__ __forceinline__ void bulk_wait0() { asm volatile("cp.async.bulk.wait_group 0;" ::: "memory"); }
__device__ __forceinline__ void l2_prefetch(const void* p, uint32_t bytes) {
  asm volatile("cp.async.bulk.prefetch.L2.global [%0], %1;" ::"l"(p), "r"(bytes) : "memory");
}

#define WG_FENCE() asm volatile("wgmma.fence.sync.aligned;" ::: "memory")
#define WG_COMMIT() asm volatile("wgmma.commit_group.sync.aligned;" ::: "memory")
#define WG_WAIT(n) asm volatile("wgmma.wait_group.sync.aligned %0;" ::"n"(n) : "memory")

#define R8(a, o) "+f"(a[o + 0]), "+f"(a[o + 1]), "+f"(a[o + 2]), "+f"(a[o + 3]), "+f"(a[o + 4]), "+f"(a[o + 5]), "+f"(a[o + 6]), "+f"(a[o + 7])
#define R32(a, o) R8(a, o), R8(a, o + 8), R8(a, o + 16), R8(a, o + 24)
#define R64(a, o) R32(a, o), R32(a, o + 32)
#define ACC64 "{%0,%1,%2,%3,%4,%5,%6,%7,%8,%9,%10,%11,%12,%13,%14,%15,%16,%17,%18,%19,%20,%21,%22,%23,%24,%25,%26,%27,%28,%29,%30,%31," \
              "%32,%33,%34,%35,%36,%37,%38,%39,%40,%41,%42,%43,%44,%45,%46,%47,%48,%49,%50,%51,%52,%53,%54,%55,%56,%57,%58,%59,%60,%61,%62,%63}"

constexpr uint32_t DESC_HI = (1024u >> 4) | (1u << 30);
__device__ __forceinline__ uint32_t desc_lo(uint32_t addr, uint32_t lbo) { return ((addr & 0x3FFFFu) >> 4) | ((lbo >> 4) << 16); }

template <int TB>
__device__ __forceinline__ void mma_ss128(float (&d)[64], uint32_t alo, uint32_t blo, int acc) {
  asm volatile("{\n.reg .pred p;\n.reg .b64 da, db;\nsetp.ne.b32 p, %66, 0;\nmov.b64 da, {%64, %68};\nmov.b64 db, {%65, %68};\n"
               "wgmma.mma_async.sync.aligned.m64n128k16.f32.bf16.bf16 " ACC64 ", da, db, p, 1, 1, 0, %67;\n}\n"
               : R64(d, 0) : "r"(alo), "r"(blo), "r"(acc), "n"(TB), "r"(DESC_HI));
}
template <int TB>
__device__ __forceinline__ void mma_rs128(float (&d)[64], uint32_t a0, uint32_t a1, uint32_t a2, uint32_t a3, uint32_t blo, int acc) {
  asm volatile("{\n.reg .pred p;\n.reg .b64 db;\nsetp.ne.b32 p, %69, 0;\nmov.b64 db, {%68, %71};\n"
               "wgmma.mma_async.sync.aligned.m64n128k16.f32.bf16.bf16 " ACC64 ", {%64,%65,%66,%67}, db, p, 1, 1, %70;\n}\n"
               : R64(d, 0) : "r"(a0), "r"(a1), "r"(a2), "r"(a3), "r"(blo), "r"(acc), "n"(TB), "r"(DESC_HI));
}
__device__ __forceinline__ void mma_ss256(float (&d)[128], uint32_t alo, uint32_t blo, int acc) {
  asm volatile("{\n.reg .pred p;\n.reg .b64 da, db;\nsetp.ne.b32 p, %130, 0;\nmov.b64 da, {%128, %131};\nmov.b64 db, {%129, %131};\n"
               "wgmma.mma_async.sync.aligned.m64n256k16.f32.bf16.bf16 "
               "{%0,%1,%2,%3,%4,%5,%6,%7,%8,%9,%10,%11,%12,%13,%14,%15,%16,%17,%18,%19,%20,%21,%22,%23,%24,%25,%26,%27,%28,%29,%30,%31,"
               "%32,%33,%34,%35,%36,%37,%38,%39,%40,%41,%42,%43,%44,%45,%46,%47,%48,%49,%50,%51,%52,%53,%54,%55,%56,%57,%58,%59,%60,%61,%62,%63,"
               "%64,%65,%66,%67,%68,%69,%70,%71,%72,%73,%74,%75,%76,%77,%78,%79,%80,%81,%82,%83,%84,%85,%86,%87,%88,%89,%90,%91,%92,%93,%94,%95,"
               "%96,%97,%98,%99,%100,%101,%102,%103,%104,%105,%106,%107,%108,%109,%110,%111,%112,%113,%114,%115,%116,%117,%118,%119,%120,%121,%122,%123,%124,%125,%126,%127},"
               " da, db, p, 1, 1, 0, 1;\n}\n"
               : R64(d, 0), R64(d, 64) : "r"(alo), "r"(blo), "r"(acc), "r"(DESC_HI));
}
template <int N>
__device__ __forceinline__ void fence_regs(float (&d)[N]) {
#pragma unroll
  for (int i = 0; i < N; i++) asm volatile("" : "+f"(d[i])::"memory");
}
__device__ __forceinline__ uint32_t pack_bf16(float lo, float hi) {
  uint32_t r; asm("cvt.rn.bf16x2.f32 %0, %1, %2;" : "=r"(r) : "f"(hi), "f"(lo)); return r;
}
__device__ __forceinline__ float bf16_round(float v) { return __bfloat162float(__float2bfloat16_rn(v)); }
__device__ __forceinline__ float bf_lo(uint32_t v) { return __uint_as_float(v << 16); }
__device__ __forceinline__ float bf_hi(uint32_t v) { return __uint_as_float(v & 0xFFFF0000u); }
__device__ __forceinline__ float ex2(float x) { float y; asm("ex2.approx.ftz.f32 %0, %1;" : "=f"(y) : "f"(x)); return y; }
__device__ __forceinline__ void stmatrix4(uint32_t addr, uint32_t r0, uint32_t r1, uint32_t r2, uint32_t r3) {
  asm volatile("stmatrix.sync.aligned.m8n8.x4.shared.b16 [%0], {%1,%2,%3,%4};" ::"r"(addr), "r"(r0), "r"(r1), "r"(r2), "r"(r3) : "memory");
}
__device__ __forceinline__ void ldmatrix4_t(uint32_t addr, uint32_t& r0, uint32_t& r1, uint32_t& r2, uint32_t& r3) {
  asm volatile("ldmatrix.sync.aligned.m8n8.x4.trans.shared.b16 {%0,%1,%2,%3}, [%4];" : "=r"(r0), "=r"(r1), "=r"(r2), "=r"(r3) : "r"(addr) : "memory");
}

struct Ring {
  uint32_t idx, phase;
  __device__ __forceinline__ void next() { if (++idx == NST) { idx = 0; phase ^= 1; } }
};

#define PROF(role, slot) do { } while (0)

struct Cons {
  uint32_t sb;
  uint32_t bars;
  int w;
  int warp;
  int lane;
  uint32_t rank;
  Ring ring;
  uint32_t stphase;
  __device__ __forceinline__ void wait_full() { mbar_wait(bars + B_FULL + ring.idx * 8, ring.phase); }
  __device__ __forceinline__ uint32_t stage_addr() { return sb + ring.idx * STAGE; }
  __device__ __forceinline__ void release(uint32_t idx) { if (lane < 2) mbar_arrive_cta(bars + B_EMPTY + idx * 8, lane); }
  __device__ __forceinline__ void turn_sync() { bar_sync(1 + w, 256); }
  __device__ __forceinline__ void turn_pass() { bar_arrive(2 - w, 256); }
  __device__ __forceinline__ void stage_out(const float (&a)[64], float s0, float s1) {
    mbar_wait(bars + B_STFREE + w * 8, stphase); stphase ^= 1;
    const int mat = lane >> 3;
    const uint32_t row = warp * 16 + (mat & 1) * 8 + (lane & 7);
    const uint32_t base = sb + SM_STG + w * 16384 + row * 128 + ((((mat >> 1) ^ lane) & 7) << 4);
#pragma unroll
    for (int jj = 0; jj < 8; jj++) {
      uint32_t r0 = pack_bf16(a[8 * jj + 0] * s0, a[8 * jj + 1] * s0), r1 = pack_bf16(a[8 * jj + 2] * s1, a[8 * jj + 3] * s1);
      uint32_t r2 = pack_bf16(a[8 * jj + 4] * s0, a[8 * jj + 5] * s0), r3 = pack_bf16(a[8 * jj + 6] * s1, a[8 * jj + 7] * s1);
      stmatrix4((base ^ (((2 * jj) & 7) << 4)) + (jj >> 2) * 8192, r0, r1, r2, r3);
    }
    fence_async_smem();
    bar_arrive(3 + w, 160);
  }
};

__device__ __forceinline__ void ln_rows(const Params& P, int row0, int lane) {
  uint4 v[2][2];
#pragma unroll
  for (int rr = 0; rr < 2; rr++) {
    const uint4* xr = reinterpret_cast<const uint4*>(P.x + (size_t)(row0 + rr) * DM);
    v[rr][0] = __ldg(xr + lane); v[rr][1] = __ldg(xr + lane + 32);
  }
  uint4 wr[2];
  wr[0] = __ldg(reinterpret_cast<const uint4*>(P.w_r) + lane); wr[1] = __ldg(reinterpret_cast<const uint4*>(P.w_r) + lane + 32);
  unsigned long long best = 0;
#pragma unroll
  for (int rr = 0; rr < 2; rr++) {
    float f[16];
#pragma unroll
    for (int c = 0; c < 2; c++) {
      const uint32_t u[4] = {v[rr][c].x, v[rr][c].y, v[rr][c].z, v[rr][c].w};
#pragma unroll
      for (int e = 0; e < 4; e++) { f[c * 8 + 2 * e] = bf_lo(u[e]); f[c * 8 + 2 * e + 1] = bf_hi(u[e]); }
    }
    float s = 0.f;
#pragma unroll
    for (int e = 0; e < 16; e++) s += f[e];
#pragma unroll
    for (int o = 16; o > 0; o >>= 1) s += __shfl_xor_sync(0xffffffffu, s, o);
    const float mean = s * (1.0f / DM);
    float q = 0.f;
#pragma unroll
    for (int e = 0; e < 16; e++) { float d = f[e] - mean; q += d * d; }
#pragma unroll
    for (int o = 16; o > 0; o >>= 1) q += __shfl_xor_sync(0xffffffffu, q, o);
    const float m = bf16_round(mean);
    const float var = bf16_round(q * (1.0f / DM));
    const float sd = bf16_round(sqrtf(bf16_round(var + 1e-5f)));
    float r = 0.f;
    const int row = row0 + rr, g = row >> 6, rl = row & 63;
#pragma unroll
    for (int c = 0; c < 2; c++) {
      const uint32_t wu[4] = {wr[c].x, wr[c].y, wr[c].z, wr[c].w};
      uint32_t o[4];
#pragma unroll
      for (int e = 0; e < 4; e++) {
        float a = bf16_round(bf16_round(f[c * 8 + 2 * e] - m) / sd), b = bf16_round(bf16_round(f[c * 8 + 2 * e + 1] - m) / sd);
        r += a * bf_lo(wu[e]); r += b * bf_hi(wu[e]);
        o[e] = pack_bf16(a, b);
      }
      const int c8 = lane + 32 * c, kh = c8 >> 3, ch = c8 & 7;
      *reinterpret_cast<uint4*>(g_xn + ((size_t)(g * 8 + kh) * 64 + rl) * 128 + ((ch ^ (rl & 7)) << 4)) = make_uint4(o[0], o[1], o[2], o[3]);
    }
#pragma unroll
    for (int o = 16; o > 0; o >>= 1) r += __shfl_xor_sync(0xffffffffu, r, o);
    uint32_t u = __float_as_uint(bf16_round(r) + 0.0f);
    u = (u & 0x80000000u) ? ~u : (u | 0x80000000u);
    unsigned long long key = ((unsigned long long)u << 32) | (unsigned long long)(0xFFFFFFFFu - (uint32_t)row);
    best = key > best ? key : best;
  }
  fence_async_all();
  __syncwarp();
  if (lane == 0) {
    atomicMax(&g_flags.key, best);
    __threadfence();
    red_release(&g_flags.ln_done, 1);
  }
}

__device__ __forceinline__ void kv_item(Cons& C) {
  uint32_t wf[128];
  {
    const int mat = C.lane >> 3;
    const uint32_t krow = (mat >> 1) * 8 + (C.lane & 7);
    const uint32_t off = C.w * 16384 + krow * 128 + (((C.warp * 2 + (mat & 1)) ^ (C.lane & 7)) << 4);
#pragma unroll
    for (int c = 0; c < 4; c++) {
      C.wait_full();
      const uint32_t st = C.stage_addr() + off;
#pragma unroll
      for (int kk = 0; kk < 8; kk++)
        ldmatrix4_t(st + kk * 2048, wf[c * 32 + kk * 4], wf[c * 32 + kk * 4 + 1], wf[c * 32 + kk * 4 + 2], wf[c * 32 + kk * 4 + 3]);
      __syncwarp();
      C.release(C.ring.idx);
      C.ring.next();
    }
  }
  float acc[64];
#pragma unroll 1
  for (int t = 0; t < 8; t++) {
    uint32_t prev = 0;
    C.turn_sync();
#pragma unroll
    for (int c = 0; c < 4; c++) {
      C.wait_full();
      const uint32_t blo = desc_lo(C.stage_addr(), 16);
      WG_FENCE();
#pragma unroll
      for (int kk = 0; kk < 8; kk++)
        mma_rs128<0>(acc, wf[c * 32 + kk * 4], wf[c * 32 + kk * 4 + 1], wf[c * 32 + kk * 4 + 2], wf[c * 32 + kk * 4 + 3],
                     blo + (((kk >> 2) * 16384 + (kk & 3) * 32) >> 4), (c | kk) != 0);
      WG_COMMIT();
      if (c == 3) C.turn_pass();
      if (c > 0) { WG_WAIT(1); C.release(prev); }
      prev = C.ring.idx;
      C.ring.next();
    }
    WG_WAIT(0);
    C.release(prev);
    fence_regs(acc);
    C.stage_out(acc, 1.0f, 1.0f);
  }
}

__device__ __forceinline__ void att_item(Cons& C, int j, bool isL) {
  constexpr float SC = 0.08838834764831845f * 1.4426950408889634f;
  float s[64], o[64];
  uint32_t q[32], p[32];
#pragma unroll
  for (int i = 0; i < 64; i++) s[i] = 0.f;
#pragma unroll 1
  for (int c = 0; c < 4; c++) {
    C.wait_full();
    const uint32_t ia = C.ring.idx, alo = desc_lo(C.stage_addr() + C.w * 16384, 16);
    C.ring.next();
    C.wait_full();
    const uint32_t ib = C.ring.idx, blo = desc_lo(C.stage_addr(), 16384);
    C.ring.next();
    C.turn_sync();
    WG_FENCE();
#pragma unroll
    for (int kk = 0; kk < 8; kk++)
      mma_ss128<1>(s, alo + (((kk >> 2) * 8192 + (kk & 3) * 32) >> 4), blo + kk * 128, 1);
    WG_COMMIT();
    C.turn_pass();
    WG_WAIT(0);
    C.release(ia); C.release(ib);
  }
  fence_regs(s);
#pragma unroll
  for (int i = 0; i < 32; i++) q[i] = pack_bf16(s[2 * i], s[2 * i + 1]);
  const int a = 2 * j + 1;
  if (!isL) { C.wait_full(); C.release(C.ring.idx); C.ring.next(); }
  float m0, m1, l0, l1;
  {
    C.wait_full();
    const uint32_t ik = C.ring.idx, klo = desc_lo(C.stage_addr(), 16384);
    C.ring.next();
    C.turn_sync();
    WG_FENCE();
#pragma unroll
    for (int kk = 0; kk < 8; kk++) mma_rs128<1>(s, q[4 * kk], q[4 * kk + 1], q[4 * kk + 2], q[4 * kk + 3], klo + kk * 128, kk != 0);
    WG_COMMIT();
    C.turn_pass();
#pragma unroll
    for (int i = 0; i < 64; i++) o[i] = 0.f;
    WG_WAIT(0);
    C.release(ik);
    fence_regs(s);
    const int odd = isL ? (1 - (int)C.rank) : (int)C.rank;
    const int lim0 = odd * 64 + C.warp * 16 + (C.lane >> 2) - 2 * (C.lane & 3);
    const int lim1 = lim0 + 8;
    m0 = -INFINITY; m1 = -INFINITY;
#pragma unroll
    for (int i = 0; i < 16; i++) {
      if (8 * i > lim0) s[4 * i] = -INFINITY;
      if (8 * i + 1 > lim0) s[4 * i + 1] = -INFINITY;
      if (8 * i > lim1) s[4 * i + 2] = -INFINITY;
      if (8 * i + 1 > lim1) s[4 * i + 3] = -INFINITY;
      m0 = fmaxf(m0, fmaxf(s[4 * i], s[4 * i + 1]));
      m1 = fmaxf(m1, fmaxf(s[4 * i + 2], s[4 * i + 3]));
    }
    m0 = fmaxf(m0, __shfl_xor_sync(0xffffffffu, m0, 1)); m1 = fmaxf(m1, __shfl_xor_sync(0xffffffffu, m1, 1));
    m0 = fmaxf(m0, __shfl_xor_sync(0xffffffffu, m0, 2)); m1 = fmaxf(m1, __shfl_xor_sync(0xffffffffu, m1, 2));
    const float c0 = -m0 * SC, c1 = -m1 * SC;
    l0 = 0.f; l1 = 0.f;
#pragma unroll
    for (int i = 0; i < 16; i++) {
      s[4 * i] = ex2(fmaf(s[4 * i], SC, c0)); s[4 * i + 1] = ex2(fmaf(s[4 * i + 1], SC, c0));
      s[4 * i + 2] = ex2(fmaf(s[4 * i + 2], SC, c1)); s[4 * i + 3] = ex2(fmaf(s[4 * i + 3], SC, c1));
      l0 += s[4 * i] + s[4 * i + 1]; l1 += s[4 * i + 2] + s[4 * i + 3];
    }
#pragma unroll
    for (int i = 0; i < 32; i++) p[i] = pack_bf16(s[2 * i], s[2 * i + 1]);
  }
  const int nb = isL ? a : a - 1;
  bool skipv = !isL;
#pragma unroll 1
  for (int n = nb - 1; n >= 0; n--) {
    if (skipv) { C.wait_full(); C.release(C.ring.idx); C.ring.next(); skipv = false; }
    C.wait_full();
    const uint32_t ik = C.ring.idx, klo = desc_lo(C.stage_addr(), 16384);
    C.ring.next();
    C.wait_full();
    const uint32_t iv = C.ring.idx, vlo = desc_lo(C.stage_addr(), 16);
    C.ring.next();
    C.turn_sync();
    WG_FENCE();
#pragma unroll
    for (int kk = 0; kk < 8; kk++) mma_rs128<1>(s, q[4 * kk], q[4 * kk + 1], q[4 * kk + 2], q[4 * kk + 3], klo + kk * 128, kk != 0);
    WG_COMMIT();
#pragma unroll
    for (int kk = 0; kk < 8; kk++)
      mma_rs128<0>(o, p[4 * kk], p[4 * kk + 1], p[4 * kk + 2], p[4 * kk + 3], vlo + (((kk >> 2) * 16384 + (kk & 3) * 32) >> 4), 1);
    WG_COMMIT();
    C.turn_pass();
    WG_WAIT(1);
    C.release(ik);
    fence_regs(s);
    float n0, n1;
    {
      float u0[4], u1[4];
#pragma unroll
      for (int i = 0; i < 4; i++) { u0[i] = fmaxf(s[4 * i], s[4 * i + 1]); u1[i] = fmaxf(s[4 * i + 2], s[4 * i + 3]); }
#pragma unroll
      for (int i = 4; i < 16; i++) {
        u0[i & 3] = fmaxf(u0[i & 3], fmaxf(s[4 * i], s[4 * i + 1]));
        u1[i & 3] = fmaxf(u1[i & 3], fmaxf(s[4 * i + 2], s[4 * i + 3]));
      }
      n0 = fmaxf(fmaxf(fmaxf(u0[0], u0[1]), fmaxf(u0[2], u0[3])), m0);
      n1 = fmaxf(fmaxf(fmaxf(u1[0], u1[1]), fmaxf(u1[2], u1[3])), m1);
    }
    n0 = fmaxf(n0, __shfl_xor_sync(0xffffffffu, n0, 1)); n1 = fmaxf(n1, __shfl_xor_sync(0xffffffffu, n1, 1));
    n0 = fmaxf(n0, __shfl_xor_sync(0xffffffffu, n0, 2)); n1 = fmaxf(n1, __shfl_xor_sync(0xffffffffu, n1, 2));
    const float a0 = ex2((m0 - n0) * SC), a1 = ex2((m1 - n1) * SC);
    m0 = n0; m1 = n1;
    const float c0 = -m0 * SC, c1 = -m1 * SC;
    float t0 = 0.f, t1 = 0.f;
#pragma unroll
    for (int i = 0; i < 16; i++) {
      s[4 * i] = ex2(fmaf(s[4 * i], SC, c0)); s[4 * i + 1] = ex2(fmaf(s[4 * i + 1], SC, c0));
      s[4 * i + 2] = ex2(fmaf(s[4 * i + 2], SC, c1)); s[4 * i + 3] = ex2(fmaf(s[4 * i + 3], SC, c1));
      t0 += s[4 * i] + s[4 * i + 1]; t1 += s[4 * i + 2] + s[4 * i + 3];
    }
    l0 = l0 * a0 + t0; l1 = l1 * a1 + t1;
    C.wait_full();
    WG_WAIT(0);
    C.release(iv);
    fence_regs(o);
    fence_regs(s);
#pragma unroll
    for (int i = 0; i < 16; i++) { o[4 * i] *= a0; o[4 * i + 1] *= a0; o[4 * i + 2] *= a1; o[4 * i + 3] *= a1; }
#pragma unroll
    for (int i = 0; i < 32; i++) p[i] = pack_bf16(s[2 * i], s[2 * i + 1]);
  }
  if (skipv) { C.wait_full(); C.release(C.ring.idx); C.ring.next(); }
  {
    C.wait_full();
    const uint32_t iv = C.ring.idx, vlo = desc_lo(C.stage_addr(), 16);
    C.ring.next();
    C.turn_sync();
    WG_FENCE();
#pragma unroll
    for (int kk = 0; kk < 8; kk++)
      mma_rs128<0>(o, p[4 * kk], p[4 * kk + 1], p[4 * kk + 2], p[4 * kk + 3], vlo + (((kk >> 2) * 16384 + (kk & 3) * 32) >> 4), 1);
    WG_COMMIT();
    C.turn_pass();
    l0 += __shfl_xor_sync(0xffffffffu, l0, 1); l1 += __shfl_xor_sync(0xffffffffu, l1, 1);
    l0 += __shfl_xor_sync(0xffffffffu, l0, 2); l1 += __shfl_xor_sync(0xffffffffu, l1, 2);
    const float r0 = 1.0f / l0, r1 = 1.0f / l1;
    WG_WAIT(0);
    C.release(iv);
    fence_regs(o);
    C.stage_out(o, r0, r1);
  }
}

__device__ __forceinline__ void op_item(Cons& C, const Params& P, int j, int nh, int ks) {
  float acc[128];
#pragma unroll
  for (int i = 0; i < 128; i++) acc[i] = 0.f;
  uint32_t pa = 0, pb = 0;
#pragma unroll 1
  for (int t = 0; t < 8; t++) {
    C.wait_full();
    const uint32_t ia = C.ring.idx, alo = desc_lo(C.stage_addr() + C.w * 16384, 16);
    C.ring.next();
    C.wait_full();
    const uint32_t i0 = C.ring.idx, b0 = desc_lo(C.stage_addr(), 8192);
    C.ring.next();
    WG_FENCE();
#pragma unroll
    for (int kk = 0; kk < 4; kk++) mma_ss256(acc, alo + kk * 2, b0 + kk * 128, 1);
    WG_COMMIT();
    if (t > 0) { WG_WAIT(1); C.release(pa); C.release(pb); }
    C.wait_full();
    const uint32_t i1 = C.ring.idx, b1 = desc_lo(C.stage_addr(), 8192);
    C.ring.next();
    WG_FENCE();
#pragma unroll
    for (int kk = 0; kk < 4; kk++) mma_ss256(acc, alo + 512 + kk * 2, b1 + kk * 128, 1);
    WG_COMMIT();
    WG_WAIT(1);
    C.release(i0);
    pa = ia; pb = i1;
  }
  const int tid = C.warp * 32 + C.lane;
  if (tid == 0) PROF(C.w, 20);
  const int g = 4 * j + 2 * (int)C.rank + C.w;
  const int kh = 4 * nh + ks;
  uint4 xv[4], nv[4];
#pragma unroll
  for (int i = 0; i < 4; i++) {
    const int idx = tid + 128 * i, row = idx >> 3, ch = (idx ^ row) & 7;
    xv[i] = __ldg(reinterpret_cast<const uint4*>(P.x + (size_t)(g * 64 + row) * DM + kh * 64 + ch * 8));
    nv[i] = __ldcg(reinterpret_cast<const uint4*>(g_xn + (size_t)(g * 8 + kh) * 8192) + idx);
  }
  const unsigned long long key = __ldcg(&g_flags.key);
  WG_WAIT(0);
  C.release(pa); C.release(pb);
  fence_regs(acc);
  const int tile = j * 2 + nh, sub = (int)C.rank * 2 + C.w;
#pragma unroll
  for (int pp = 1; pp < 4; pp++) {
    float4* dst = g_exch + (size_t)(((tile * 4 + ((pp + ks) & 3)) * 3 + (pp - 1)) * 4 + sub) * 1024 + tid;
#pragma unroll
    for (int v = 0; v < 8; v++)
      __stcg(dst + v * 128, make_float4(acc[32 * pp + 4 * v], acc[32 * pp + 4 * v + 1], acc[32 * pp + 4 * v + 2], acc[32 * pp + 4 * v + 3]));
  }
  if (tid == 0) PROF(C.w, 21);
  bar_sync(6 + C.w, 128);
  if (tid == 0) {
    PROF(C.w, 22);
    __threadfence();
#pragma unroll
    for (int pp = 1; pp < 4; pp++) red_release(&g_flags.ex_done[(tile * 4 + ((pp + ks) & 3)) * 4 + sub], 1);
    PROF(C.w, 23);
    flag_wait(&g_flags.ex_done[(tile * 4 + ks) * 4 + sub], 3);
    PROF(C.w, 24);
  }
  bar_sync(6 + C.w, 128);
#pragma unroll
  for (int pp = 1; pp < 4; pp++) {
    const float4* src = g_exch + (size_t)(((tile * 4 + ks) * 3 + (pp - 1)) * 4 + sub) * 1024 + tid;
#pragma unroll
    for (int v = 0; v < 8; v++) {
      const float4 f = __ldcg(src + v * 128);
      acc[4 * v] += f.x; acc[4 * v + 1] += f.y; acc[4 * v + 2] += f.z; acc[4 * v + 3] += f.w;
    }
  }
  mbar_wait(C.bars + B_STFREE + C.w * 8, C.stphase);
  const uint32_t stg = C.sb + SM_STG + C.w * 16384;
  {
    const int mat = C.lane >> 3;
    const uint32_t row = C.warp * 16 + (mat & 1) * 8 + (C.lane & 7);
    const uint32_t base = stg + row * 128 + ((((mat >> 1) ^ C.lane) & 7) << 4);
#pragma unroll
    for (int jj = 0; jj < 4; jj++)
      stmatrix4(base ^ ((2 * jj) << 4), pack_bf16(acc[8 * jj], acc[8 * jj + 1]), pack_bf16(acc[8 * jj + 2], acc[8 * jj + 3]),
                pack_bf16(acc[8 * jj + 4], acc[8 * jj + 5]), pack_bf16(acc[8 * jj + 6], acc[8 * jj + 7]));
  }
  bar_sync(6 + C.w, 128);
  const int sel = (int)(0xFFFFFFFFu - (uint32_t)key);
#pragma unroll
  for (int i = 0; i < 4; i++) {
    const int idx = tid + 128 * i, row = idx >> 3, ch = (idx ^ row) & 7;
    uint4 av;
    asm volatile("ld.shared.v4.u32 {%0,%1,%2,%3}, [%4];" : "=r"(av.x), "=r"(av.y), "=r"(av.z), "=r"(av.w) : "r"(stg + idx * 16) : "memory");
    const uint32_t au[4] = {av.x, av.y, av.z, av.w}, xu[4] = {xv[i].x, xv[i].y, xv[i].z, xv[i].w};
    uint32_t nu[4] = {nv[i].x, nv[i].y, nv[i].z, nv[i].w};
    if (g * 64 + row == sel) {
      flag_wait(&g_flags.moe_done, 4);
      uint32_t ub = (uint32_t)(key >> 32);
      ub = (ub & 0x80000000u) ? (ub & 0x7FFFFFFFu) : ~ub;
      const float sig = bf16_round(1.0f / (1.0f + expf(-__uint_as_float(ub))));
#pragma unroll
      for (int e = 0; e < 4; e++) {
        const int col = kh * 64 + ch * 8 + 2 * e;
        float y0 = 0.f, y1 = 0.f;
#pragma unroll
        for (int c = 0; c < 4; c++) { y0 += __ldcg(&g_ypart[c * DM + col]); y1 += __ldcg(&g_ypart[c * DM + col + 1]); }
        y0 = bf16_round(bf16_round(y0) * sig); y1 = bf16_round(bf16_round(y1) * sig);
        nu[e] = pack_bf16(bf_lo(nu[e]) + y0, bf_hi(nu[e]) + y1);
      }
    }
    uint32_t ou[4];
#pragma unroll
    for (int e = 0; e < 4; e++)
      ou[e] = pack_bf16(bf16_round(bf_lo(xu[e]) + bf_lo(au[e])) + bf_lo(nu[e]), bf16_round(bf_hi(xu[e]) + bf_hi(au[e])) + bf_hi(nu[e]));
    *reinterpret_cast<uint4*>(P.out + (size_t)(g * 64 + row) * DM + kh * 64 + ch * 8) = make_uint4(ou[0], ou[1], ou[2], ou[3]);
  }
}

__device__ __forceinline__ void moe_item(Cons& C, const Params& P, int part, unsigned char* smem) {
  const int tid = C.w * 128 + C.warp * 32 + C.lane;
  float* xs = reinterpret_cast<float*>(smem + SM_STG);
  float* hs = xs + 512;
  float* red = xs + 1024;
  if (tid == 0) flag_wait(&g_flags.ln_done, 1024);
  bar_sync(5, 256);
  const unsigned long long key = __ldcg(&g_flags.key);
  const int sel = (int)(0xFFFFFFFFu - (uint32_t)key);
  {
    const int g = sel >> 6, rl = sel & 63;
    const int c2 = tid * 2, kh = c2 >> 6, ch = (c2 >> 3) & 7;
    const uint32_t u = __ldcg(reinterpret_cast<const uint32_t*>(g_xn + ((size_t)(g * 8 + kh) * 64 + rl) * 128 + ((ch ^ (rl & 7)) << 4) + (c2 & 7) * 2));
    xs[c2] = bf_lo(u); xs[c2 + 1] = bf_hi(u);
  }
  bar_sync(5, 256);
  if (tid < 224) {
    const int chunk = tid % 56, kg = tid / 56;
    const uint4* wg = reinterpret_cast<const uint4*>(P.w_gate + (size_t)kg * 128 * FF + part * 448 + chunk * 8);
    const uint4* wu = reinterpret_cast<const uint4*>(P.w_up + (size_t)kg * 128 * FF + part * 448 + chunk * 8);
    float ag[8], au[8];
#pragma unroll
    for (int e = 0; e < 8; e++) { ag[e] = 0.f; au[e] = 0.f; }
#pragma unroll 1
    for (int k0 = 0; k0 < 128; k0 += 16) {
      uint4 vg[16], vu[16];
#pragma unroll
      for (int i = 0; i < 16; i++) { vg[i] = __ldg(wg + (size_t)(k0 + i) * (FF / 8)); vu[i] = __ldg(wu + (size_t)(k0 + i) * (FF / 8)); }
#pragma unroll
      for (int i = 0; i < 16; i++) {
        const float xk = xs[kg * 128 + k0 + i];
        const uint32_t a[4] = {vg[i].x, vg[i].y, vg[i].z, vg[i].w}, b[4] = {vu[i].x, vu[i].y, vu[i].z, vu[i].w};
#pragma unroll
        for (int e = 0; e < 4; e++) {
          ag[2 * e] += xk * bf_lo(a[e]); ag[2 * e + 1] += xk * bf_hi(a[e]);
          au[2 * e] += xk * bf_lo(b[e]); au[2 * e + 1] += xk * bf_hi(b[e]);
        }
      }
    }
#pragma unroll
    for (int e = 0; e < 8; e++) { red[(kg * 2) * 448 + chunk * 8 + e] = ag[e]; red[(kg * 2 + 1) * 448 + chunk * 8 + e] = au[e]; }
  }
  bar_sync(5, 256);
  for (int f = tid; f < 448; f += 256) {
    float gs = 0.f, us = 0.f;
#pragma unroll
    for (int kg = 0; kg < 4; kg++) { gs += red[(kg * 2) * 448 + f]; us += red[(kg * 2 + 1) * 448 + f]; }
    gs = bf16_round(gs); us = bf16_round(us);
    const float sl = bf16_round(gs / (1.0f + expf(-gs)));
    hs[f] = bf16_round(sl * us);
  }
  bar_sync(5, 256);
  {
    const int chunk = tid & 63, rg = tid >> 6;
    const uint4* wd = reinterpret_cast<const uint4*>(P.w_down + (size_t)(part * 448 + rg * 112) * DM + chunk * 8);
    float ay[8];
#pragma unroll
    for (int e = 0; e < 8; e++) ay[e] = 0.f;
#pragma unroll 1
    for (int k0 = 0; k0 < 112; k0 += 28) {
      uint4 v[28];
#pragma unroll
      for (int i = 0; i < 28; i++) v[i] = __ldg(wd + (size_t)(k0 + i) * (DM / 8));
#pragma unroll
      for (int i = 0; i < 28; i++) {
        const float hk = hs[rg * 112 + k0 + i];
        const uint32_t a[4] = {v[i].x, v[i].y, v[i].z, v[i].w};
#pragma unroll
        for (int e = 0; e < 4; e++) { ay[2 * e] += hk * bf_lo(a[e]); ay[2 * e + 1] += hk * bf_hi(a[e]); }
      }
    }
#pragma unroll
    for (int e = 0; e < 8; e++) red[rg * 512 + chunk * 8 + e] = ay[e];
  }
  bar_sync(5, 256);
  for (int c = tid; c < DM; c += 256) g_ypart[part * DM + c] = red[c] + red[512 + c] + red[1024 + c] + red[1536 + c];
  bar_sync(5, 256);
  if (tid == 0) { __threadfence(); red_release(&g_flags.moe_done, 1); }
}

__global__ void __launch_bounds__(384, 1) mega_kernel(const __grid_constant__ Params P) {
  extern __shared__ unsigned char smem_raw[];
  const uint32_t sraw = smem_u32(smem_raw);
  const uint32_t sb = (sraw + 1023u) & ~1023u;
  const uint32_t bars = sb + SM_BAR;
  const int warp_id = __shfl_sync(0xffffffffu, threadIdx.x >> 5, 0);
  const int lane = threadIdx.x & 31;
  uint32_t rank; asm volatile("mov.u32 %0, %%cluster_ctarank;" : "=r"(rank));
  const int pair = blockIdx.x >> 1;

  if (threadIdx.x == 0) {
    for (int s = 0; s < NST; s++) { mbar_init(bars + B_FULL + s * 8, 1); mbar_init(bars + B_EMPTY + s * 8, 16); }
    mbar_init(bars + B_STFREE, 1); mbar_init(bars + B_STFREE + 8, 1);
    mbar_init(bars + B_DONE, 11);
    asm volatile("fence.mbarrier_init.release.cluster;" ::: "memory");
  }
  __syncthreads();
  asm volatile("barrier.cluster.arrive.aligned;\nbarrier.cluster.wait.aligned;" ::: "memory");

  if (warp_id < 4) {
    asm volatile("setmaxnreg.dec.sync.aligned.u32 40;");
    if (warp_id == 0) {
      if (lane == 0) {
        Ring ring{0, 1};
        auto acquire = [&]() -> uint32_t {
          mbar_wait(bars + B_EMPTY + ring.idx * 8, ring.phase);
          mbar_expect_tx(bars + B_FULL + ring.idx * 8, STAGE);
          return sb + ring.idx * STAGE;
        };
        int natt = 0;
        bool ln_ok = false;
        for (int it = 0; it < MAXIT; it++) {
          const uint32_t d = P.items[pair][it];
          const int type = d & 255, a = (d >> 8) & 255, b = (d >> 16) & 255, c3 = d >> 24;
          if (type == IT_END) break;
          PROF(2, it * 2);
          if (type == IT_KV) {
            const CUtensorMap* tw = rank ? &P.tm_wuv : &P.tm_wuk;
            for (int c = 0; c < 4; c++) {
              const uint32_t dst = acquire(), fb = bars + B_FULL + ring.idx * 8;
              tma_load(dst, tw, a * 128, c * 128, fb);
              tma_load(dst + 16384, tw, a * 128 + 64, c * 128, fb);
              ring.next();
            }
            for (int t = 0; t < 32; t++) {
              const uint32_t dst = acquire(), fb = bars + B_FULL + ring.idx * 8;
              tma_load_mc(dst + rank * 16384, &P.tm_ckv, (t & 3) * 128 + rank * 64, b * 1024 + (t >> 2) * 128, fb);
              ring.next();
            }
          } else if (type == IT_ATT) {
            const int h = a, j = b;
            if (!ln_ok) { flag_wait(&g_flags.ln_done, 1024); fence_async_all(); ln_ok = true; }
            const int gL = 4 * j + 3 - (int)rank, gS = 4 * j + (int)rank;
            const int g0 = (natt & 1) ? gS : gL, g1 = (natt & 1) ? gL : gS;
            natt++;
            for (int c = 0; c < 4; c++) {
              uint32_t dst = acquire(), fb = bars + B_FULL + ring.idx * 8;
              bulk_load(dst, g_xn + (size_t)(g0 * 8 + 2 * c) * 8192, 16384, fb);
              bulk_load(dst + 16384, g_xn + (size_t)(g1 * 8 + 2 * c) * 8192, 16384, fb);
              ring.next();
              dst = acquire(); fb = bars + B_FULL + ring.idx * 8;
              tma_load_mc(dst + rank * 16384, &P.tm_wq, h * 128 + rank * 64, c * 128, fb);
              ring.next();
            }
            flag_wait(&g_flags.kv_done[h * 2], 4);
            if (j >= 4) flag_wait(&g_flags.kv_done[h * 2 + 1], 4);
            fence_async_all();
            PROF(2, it * 2 + 1);
            const unsigned char* kb = g_kv + (size_t)h * 2 * 16 * 32768 + rank * 16384;
            const unsigned char* vb = kb + 16 * 32768;
            for (int n = 2 * j + 1; n >= -1; n--) {
              if (n >= 0) {
                const uint32_t dst = acquire(), fb = bars + B_FULL + ring.idx * 8;
                bulk_load_mc(dst + rank * 16384, kb + (size_t)n * 32768, 16384, fb);
                ring.next();
              }
              if (n < 2 * j + 1) {
                const uint32_t dst = acquire(), fb = bars + B_FULL + ring.idx * 8;
                bulk_load_mc(dst + rank * 16384, vb + (size_t)(n + 1) * 32768, 16384, fb);
                ring.next();
              }
            }
          } else if (type == IT_OP) {
            const int j = a, nh = b, ks = c3;
            for (int t = 0; t < 8; t++) {
              const int hh = P.korder[j][ks * 8 + t];
              flag_wait(&g_flags.ctx_done[j * 32 + hh], 4);
              PROF(2, 20 + t);
              fence_async_all();
              uint32_t dst = acquire(), fb = bars + B_FULL + ring.idx * 8;
              const unsigned char* src = g_ctx + ((size_t)(4 * j + 2 * rank) * 32 + hh) * 16384;
              bulk_load(dst, src, 16384, fb);
              bulk_load(dst + 16384, src + (size_t)32 * 16384, 16384, fb);
              ring.next();
              for (int bb = 0; bb < 2; bb++) {
                dst = acquire(); fb = bars + B_FULL + ring.idx * 8;
                tma_load_mc(dst + rank * 16384, &P.tm_wo, nh * 256 + ((2 * rank + ks) & 3) * 64, hh * 128 + bb * 64, fb);
                tma_load_mc(dst + rank * 16384 + 8192, &P.tm_wo, nh * 256 + ((2 * rank + 1 + ks) & 3) * 64, hh * 128 + bb * 64, fb);
                ring.next();
              }
            }
          }
        }
      }
      __syncwarp();
      if (lane == 0) mbar_arrive(bars + B_DONE);
    } else if (warp_id < 3) {
      const int w = warp_id - 1;
      const uint32_t stg = sb + SM_STG + w * 16384;
      int natt = 0;
      for (int it = 0; it < MAXIT; it++) {
        const uint32_t d = P.items[pair][it];
        const int type = d & 255, a = (d >> 8) & 255, b = (d >> 16) & 255;
        if (type == IT_END) break;
        if (type == IT_KV) {
          unsigned char* dst = g_kv + ((size_t)(a * 2 + rank) * 16 + b * 8) * 32768 + w * 8192;
          for (int t = 0; t < 8; t++) {
            bar_sync(3 + w, 160);
            if (lane == 0) {
              bulk_store(dst + (size_t)t * 32768, stg, 8192);
              bulk_store(dst + (size_t)t * 32768 + 16384, stg + 8192, 8192);
              bulk_commit();
              bulk_wait_read0();
              mbar_arrive(bars + B_STFREE + w * 8);
              if (t == 7) { bulk_wait0(); fence_async_all(); __threadfence(); red_release(&g_flags.kv_done[a * 2 + b], 1); }
            }
            __syncwarp();
          }
        } else if (type == IT_ATT) {
          const bool isL = ((natt & 1) == w);
          natt++;
          const int g = 4 * b + (isL ? 3 - (int)rank : (int)rank);
          bar_sync(3 + w, 160);
          if (lane == 0) {
            bulk_store(g_ctx + ((size_t)g * 32 + a) * 16384, stg, 16384);
            bulk_commit();
            bulk_wait_read0();
            mbar_arrive(bars + B_STFREE + w * 8);
            bulk_wait0(); fence_async_all(); __threadfence();
            red_release(&g_flags.ctx_done[b * 32 + a], 1);
          }
          __syncwarp();
        }
      }
      if (lane == 0) mbar_arrive(bars + B_DONE);
    } else {
      if (lane == 0) {
        uint32_t t0 = clk32();
        while (!mbar_try(bars + B_DONE, 0)) { __nanosleep(200); if (clk32() - t0 > TIMEOUT_CLKS) __trap(); }
      }
      __syncwarp();
    }
    asm volatile("barrier.cluster.arrive.aligned;\nbarrier.cluster.wait.aligned;" ::: "memory");
    if (threadIdx.x == 0) {
      __threadfence();
      if (atomicAdd(&g_flags.exit_cnt, 1) == NCTA - 1) {
        g_flags.key = 0; g_flags.ln_done = 0; g_flags.moe_done = 0;
        for (int i = 0; i < 64; i++) g_flags.kv_done[i] = 0;
        for (int i = 0; i < 256; i++) { g_flags.ctx_done[i] = 0; g_flags.ex_done[i] = 0; }
        __threadfence();
        g_flags.exit_cnt = 0;
      }
    }
  } else {
    asm volatile("setmaxnreg.inc.sync.aligned.u32 232;");
    Cons C;
    C.sb = sb; C.bars = bars; C.w = (warp_id - 4) >> 2; C.warp = warp_id & 3; C.lane = lane; C.rank = rank;
    C.ring = Ring{0, 0}; C.stphase = 1;
    if (C.w == 1) bar_arrive(1, 256);
    if (threadIdx.x % 128 == 0) PROF(C.w, 62);
    if (blockIdx.x < 128) ln_rows(P, blockIdx.x * 16 + (warp_id - 4) * 2, lane);
    int natt = 0;
    for (int it = 0; it < MAXIT; it++) {
      const uint32_t d = P.items[pair][it];
      const int type = d & 255, a = (d >> 8) & 255, b = (d >> 16) & 255, c3 = d >> 24;
      if (threadIdx.x % 128 == 0) PROF(C.w, it);
      if (type == IT_END) break;
      if (type == IT_KV) kv_item(C);
      if (type == IT_ATT) { att_item(C, b, (natt & 1) == C.w); natt++; }
      if (type == IT_OP) op_item(C, P, a, b, c3);
      if (type == IT_MOE) moe_item(C, P, a * 2 + (int)rank, smem_raw + (sb - sraw));
    }
    if ((natt & 1) == C.w) C.turn_sync();
    __syncwarp();
    if (lane == 0) mbar_arrive(bars + B_DONE);
    asm volatile("barrier.cluster.arrive.aligned;\nbarrier.cluster.wait.aligned;" ::: "memory");
  }
}

typedef CUresult (*EncodeFn)(CUtensorMap*, CUtensorMapDataType, cuuint32_t, void*, const cuuint64_t*, const cuuint64_t*, const cuuint32_t*,
                             const cuuint32_t*, CUtensorMapInterleave, CUtensorMapSwizzle, CUtensorMapL2promotion, CUtensorMapFloatOOBfill);

void make_map(EncodeFn enc, CUtensorMap* tm, const void* ptr, int cols, int rows, int box_rows) {
  cuuint64_t dims[2] = {(cuuint64_t)cols, (cuuint64_t)rows};
  cuuint64_t strides[1] = {(cuuint64_t)cols * 2};
  cuuint32_t box[2] = {64, (cuuint32_t)box_rows};
  cuuint32_t es[2] = {1, 1};
  enc(tm, CU_TENSOR_MAP_DATA_TYPE_BFLOAT16, 2, const_cast<void*>(ptr), dims, strides, box, es, CU_TENSOR_MAP_INTERLEAVE_NONE,
      CU_TENSOR_MAP_SWIZZLE_128B, CU_TENSOR_MAP_L2_PROMOTION_L2_256B, CU_TENSOR_MAP_FLOAT_OOB_FILL_NONE);
}

void build_schedule(Params& P) {
  memset(P.items, 0, sizeof(P.items));
  static const int lanes[2][4] = {{7, 4, 3, 0}, {6, 5, 2, 1}};
  int fin[8][32];
  for (int p = 0; p < 64; p++) {
    const int h = p >> 1;
    int n = 0, t = 0;
    P.items[p][n++] = IT_KV | (h << 8) | ((p & 1) << 16);
    for (int i = 0; i < 4; i++) {
      const int j = lanes[p & 1][(i + h) & 3];
      P.items[p][n++] = IT_ATT | (h << 8) | (j << 16);
      t += 4 * j + 8;
      fin[j][h] = t;
    }
    const int j = p >> 3, nh = (p >> 2) & 1, ks = p & 3;
    P.items[p][n++] = IT_OP | (j << 8) | (nh << 16) | (ks << 24);
  }
  P.items[64][0] = IT_MOE | (0 << 8);
  P.items[65][0] = IT_MOE | (1 << 8);
  for (int j = 0; j < 8; j++) {
    int ord[32];
    for (int h = 0; h < 32; h++) ord[h] = h;
    for (int x = 1; x < 32; x++)
      for (int y = x; y > 0 && fin[j][ord[y]] < fin[j][ord[y - 1]]; y--) { int tmp = ord[y]; ord[y] = ord[y - 1]; ord[y - 1] = tmp; }
    for (int r = 0; r < 32; r++) P.korder[j][(r & 3) * 8 + (r >> 2)] = (uint8_t)ord[r];
  }
}

}

extern "C" void kernel_launch(void* const* d_in, const int* in_sizes, int n_in, void* d_out, int out_size) {
  (void)in_sizes; (void)n_in; (void)out_size;
  static EncodeFn enc = nullptr;
  if (!enc) {
    void* fn = nullptr;
    cudaDriverEntryPointQueryResult qr;
    cudaGetDriverEntryPoint("cuTensorMapEncodeTiled", &fn, cudaEnableDefault, &qr);
    enc = (EncodeFn)fn;
    cudaFuncSetAttribute(mega_kernel, cudaFuncAttributeMaxDynamicSharedMemorySize, SMEM_BYTES);
  }
  Params P;
  make_map(enc, &P.tm_ckv, d_in[1], 512, 2048, 128);
  make_map(enc, &P.tm_wq, d_in[2], 4096, 512, 128);
  make_map(enc, &P.tm_wuk, d_in[3], 4096, 512, 128);
  make_map(enc, &P.tm_wuv, d_in[4], 4096, 512, 128);
  make_map(enc, &P.tm_wo, d_in[5], 512, 4096, 64);
  P.x = (const __nv_bfloat16*)d_in[0];
  P.w_r = (const __nv_bfloat16*)d_in[7];
  P.w_gate = (const __nv_bfloat16*)d_in[8];
  P.w_up = (const __nv_bfloat16*)d_in[9];
  P.w_down = (const __nv_bfloat16*)d_in[10];
  P.out = (__nv_bfloat16*)d_out;
  build_schedule(P);
  cudaLaunchConfig_t cfg = {};
  cfg.gridDim = dim3(NCTA); cfg.blockDim = dim3(384); cfg.dynamicSmemBytes = SMEM_BYTES; cfg.stream = cudaStreamPerThread;
  cudaLaunchAttribute at[1];
  at[0].id = cudaLaunchAttributeClusterDimension; at[0].val.clusterDim.x = 2; at[0].val.clusterDim.y = 1; at[0].val.clusterDim.z = 1;
  cfg.attrs = at; cfg.numAttrs = 1;
  cudaLaunchKernelEx(&cfg, mega_kernel, P);
}
```

```cpp
#include <cuda_runtime.h>
#include <cuda_bf16.h>
#include <cuda.h>
#include <stdint.h>
#include <limits.h>
#include <type_traits>

namespace {

constexpr int DM = 512, NH = 32, FF = 1792;
constexpr int NCTA = 132;
constexpr int NST = 6;
constexpr uint32_t STAGE = 32768;
constexpr uint32_t SM_STG = NST * STAGE;
constexpr uint32_t SM_BAR = SM_STG + 32768;
constexpr uint32_t SMEM_BYTES = SM_BAR + 256 + 1024;
constexpr uint32_t B_FULL = 0, B_EMPTY = 64, B_STFREE = 128, B_DONE = 144;

struct alignas(64) Params {
  CUtensorMap tm_ckv, tm_wq, tm_wuk, tm_wuv, tm_wo;
  const __nv_bfloat16 *x, *w_q, *w_uk, *w_uv, *w_o, *w_r, *w_gate, *w_up, *w_down;
  __nv_bfloat16* out;
};

struct Flags {
  unsigned long long key[2]; unsigned pad0[28];
  unsigned exit_cnt; unsigned pad1[31];
  unsigned ln_done; unsigned pad2[31];
  unsigned moe_done; unsigned pad3[31];
  unsigned kv_done[32];
  unsigned q_done[32];
  unsigned ctx_done[256];
  unsigned ex_done[1024];
};

__device__ Flags g_flags;
__device__ __align__(1024) unsigned char g_kv[(size_t)NH * 2 * 16 * 32768];
__device__ __align__(1024) unsigned char g_xn[(size_t)32 * 8 * 8192];
__device__ __align__(1024) unsigned char g_qc[(size_t)32 * NH * 16384];
__device__ __align__(1024) uint4 g_exch[(size_t)16 * 4 * 3 * 4 * 512];
__device__ float g_ypart[4 * DM];

__device__ __forceinline__ uint32_t smem_u32(const void* p) { return (uint32_t)__cvta_generic_to_shared(p); }
__device__ __forceinline__ void mbar_init(uint32_t bar, int cnt) {
  asm volatile("mbarrier.init.shared::cta.b64 [%0], %1;" ::"r"(bar), "r"(cnt) : "memory");
}
__device__ __forceinline__ void mbar_expect_tx(uint32_t bar, uint32_t bytes) {
  asm volatile("mbarrier.arrive.expect_tx.shared::cta.b64 _, [%0], %1;" ::"r"(bar), "r"(bytes) : "memory");
}
__device__ __forceinline__ void mbar_arrive(uint32_t bar) {
  asm volatile("mbarrier.arrive.shared::cta.b64 _, [%0];" ::"r"(bar) : "memory");
}
__device__ __forceinline__ uint32_t mapa(uint32_t addr, uint32_t cta) {
  uint32_t r; asm volatile("mapa.shared::cluster.u32 %0, %1, %2;" : "=r"(r) : "r"(addr), "r"(cta)); return r;
}
__device__ __forceinline__ void mbar_arrive_cluster(uint32_t bar, uint32_t cnt) {
  asm volatile("mbarrier.arrive.shared::cluster.b64 _, [%0], %1;" ::"r"(bar), "r"(cnt) : "memory");
}
__device__ __forceinline__ uint32_t mbar_test2(uint32_t b0, uint32_t p0, uint32_t b1, uint32_t p1) {
  uint32_t ok;
  asm volatile("{\n.reg .pred p, q;\nmbarrier.test_wait.parity.shared::cta.b64 p, [%1], %2;\nmbarrier.test_wait.parity.shared::cta.b64 q, [%3], %4;\n"
               "and.pred p, p, q;\nselp.u32 %0, 1, 0, p;\n}\n" : "=r"(ok) : "r"(b0), "r"(p0), "r"(b1), "r"(p1) : "memory");
  return ok;
}
__device__ __forceinline__ bool mbar_try(uint32_t bar, uint32_t parity) {
  uint32_t ok;
  asm volatile("{\n.reg .pred p;\nmbarrier.try_wait.parity.shared::cta.b64 p, [%1], %2;\nselp.u32 %0, 1, 0, p;\n}\n"
               : "=r"(ok) : "r"(bar), "r"(parity) : "memory");
  return ok != 0;
}
__device__ __forceinline__ uint32_t clk32() { uint32_t c; asm volatile("mov.u32 %0, %%clock;" : "=r"(c)); return c; }
constexpr uint32_t TIMEOUT_CLKS = 1u << 30;
__device__ __forceinline__ void mbar_wait(uint32_t bar, uint32_t parity) {
  asm volatile("{\n.reg .pred p;\nWAIT_LOOP:\nmbarrier.try_wait.parity.shared::cta.b64 p, [%0], %1;\n@p bra WAIT_DONE;\nbra WAIT_LOOP;\nWAIT_DONE:\n}\n"
               ::"r"(bar), "r"(parity) : "memory");
}
__device__ __forceinline__ unsigned ld_acquire(const unsigned* p) {
  unsigned v; asm volatile("ld.acquire.gpu.global.u32 %0, [%1];" : "=r"(v) : "l"(p) : "memory"); return v;
}
__device__ __forceinline__ void red_release(unsigned* p, unsigned v) {
  asm volatile("red.release.gpu.global.add.u32 [%0], %1;" ::"l"(p), "r"(v) : "memory");
}
__device__ __forceinline__ void red_relaxed(unsigned* p, unsigned v) {
  asm volatile("red.relaxed.gpu.global.add.u32 [%0], %1;" ::"l"(p), "r"(v) : "memory");
}
__device__ __forceinline__ bool flag_ok(const unsigned* p, unsigned target) { return (int)(ld_acquire(p) - target) >= 0; }
__device__ __forceinline__ void flag_wait(const unsigned* p, unsigned target) {
  while (!flag_ok(p, target)) { __nanosleep(40); }
}
__device__ __forceinline__ void fence_gpu() { asm volatile("fence.acq_rel.gpu;" ::: "memory"); }
__device__ __forceinline__ void fence_async_global() { asm volatile("fence.proxy.async.global;" ::: "memory"); }
__device__ __forceinline__ void fence_async_smem() { asm volatile("fence.proxy.async.shared::cta;" ::: "memory"); }
__device__ __forceinline__ void bar_sync(int id, int n) { asm volatile("bar.sync %0, %1;" ::"r"(id), "r"(n) : "memory"); }
__device__ __forceinline__ void bar_arrive(int id, int n) { asm volatile("bar.arrive %0, %1;" ::"r"(id), "r"(n) : "memory"); }

__device__ __forceinline__ void bulk_load(uint32_t dst, const void* src, uint32_t bytes, uint32_t bar) {
  asm volatile("cp.async.bulk.shared::cluster.global.mbarrier::complete_tx::bytes [%0], [%1], %2, [%3];"
               ::"r"(dst), "l"(src), "r"(bytes), "r"(bar) : "memory");
}
__device__ __forceinline__ void bulk_load_mc(uint32_t dst, const void* src, uint32_t bytes, uint32_t bar) {
  asm volatile("cp.async.bulk.shared::cluster.global.mbarrier::complete_tx::bytes.multicast::cluster [%0], [%1], %2, [%3], %4;"
               ::"r"(dst), "l"(src), "r"(bytes), "r"(bar), "h"((uint16_t)3) : "memory");
}
__device__ __forceinline__ void tma_load(uint32_t dst, const CUtensorMap* tm, int c0, int c1, uint32_t bar) {
  asm volatile("cp.async.bulk.tensor.2d.shared::cluster.global.mbarrier::complete_tx::bytes [%0], [%1, {%3, %4}], [%2];"
               ::"r"(dst), "l"(tm), "r"(bar), "r"(c0), "r"(c1) : "memory");
}
__device__ __forceinline__ void tma_load_mc(uint32_t dst, const CUtensorMap* tm, int c0, int c1, uint32_t bar) {
  asm volatile("cp.async.bulk.tensor.2d.shared::cluster.global.mbarrier::complete_tx::bytes.multicast::cluster [%0], [%1, {%3, %4}], [%2], %5;"
               ::"r"(dst), "l"(tm), "r"(bar), "r"(c0), "r"(c1), "h"((uint16_t)3) : "memory");
}
__device__ __forceinline__ void bulk_store(void* dst, uint32_t src, uint32_t bytes) {
  asm volatile("cp.async.bulk.global.shared::cta.bulk_group [%0], [%1], %2;" ::"l"(dst), "r"(src), "r"(bytes) : "memory");
}
__device__ __forceinline__ void bulk_commit() { asm volatile("cp.async.bulk.commit_group;" ::: "memory"); }
__device__ __forceinline__ void bulk_wait_read0() { asm volatile("cp.async.bulk.wait_group.read 0;" ::: "memory"); }
__device__ __forceinline__ void bulk_wait0() { asm volatile("cp.async.bulk.wait_group 0;" ::: "memory"); }
__device__ __forceinline__ void l2_prefetch(const void* p, uint32_t bytes) {
  asm volatile("cp.async.bulk.prefetch.L2.global [%0], %1;" ::"l"(p), "r"(bytes) : "memory");
}

#define WG_FENCE() asm volatile("wgmma.fence.sync.aligned;" ::: "memory")
#define WG_COMMIT() asm volatile("wgmma.commit_group.sync.aligned;" ::: "memory")
#define WG_WAIT(n) asm volatile("wgmma.wait_group.sync.aligned %0;" ::"n"(n) : "memory")

#define R8(a, o) "+f"(a[o + 0]), "+f"(a[o + 1]), "+f"(a[o + 2]), "+f"(a[o + 3]), "+f"(a[o + 4]), "+f"(a[o + 5]), "+f"(a[o + 6]), "+f"(a[o + 7])
#define R32(a, o) R8(a, o), R8(a, o + 8), R8(a, o + 16), R8(a, o + 24)
#define R64(a, o) R32(a, o), R32(a, o + 32)
#define ACC64 "{%0,%1,%2,%3,%4,%5,%6,%7,%8,%9,%10,%11,%12,%13,%14,%15,%16,%17,%18,%19,%20,%21,%22,%23,%24,%25,%26,%27,%28,%29,%30,%31," \
              "%32,%33,%34,%35,%36,%37,%38,%39,%40,%41,%42,%43,%44,%45,%46,%47,%48,%49,%50,%51,%52,%53,%54,%55,%56,%57,%58,%59,%60,%61,%62,%63}"

constexpr uint32_t DESC_HI = (1024u >> 4) | (1u << 30);
__device__ __forceinline__ uint32_t desc_lo(uint32_t addr, uint32_t lbo) { return ((addr & 0x3FFFFu) >> 4) | ((lbo >> 4) << 16); }

template <int TB>
__device__ __forceinline__ void mma_rs128(float (&d)[64], uint32_t a0, uint32_t a1, uint32_t a2, uint32_t a3, uint32_t blo, int acc) {
  asm volatile("{\n.reg .pred p;\n.reg .b64 db;\nsetp.ne.b32 p, %69, 0;\nmov.b64 db, {%68, %71};\n"
               "wgmma.mma_async.sync.aligned.m64n128k16.f32.bf16.bf16 " ACC64 ", {%64,%65,%66,%67}, db, p, 1, 1, %70;\n}\n"
               : R64(d, 0) : "r"(a0), "r"(a1), "r"(a2), "r"(a3), "r"(blo), "r"(acc), "n"(TB), "r"(DESC_HI));
}
__device__ __forceinline__ void mma_ss256(float (&d)[128], uint32_t alo, uint32_t blo, int acc) {
  asm volatile("{\n.reg .pred p;\n.reg .b64 da, db;\nsetp.ne.b32 p, %130, 0;\nmov.b64 da, {%128, %131};\nmov.b64 db, {%129, %131};\n"
               "wgmma.mma_async.sync.aligned.m64n256k16.f32.bf16.bf16 "
               "{%0,%1,%2,%3,%4,%5,%6,%7,%8,%9,%10,%11,%12,%13,%14,%15,%16,%17,%18,%19,%20,%21,%22,%23,%24,%25,%26,%27,%28,%29,%30,%31,"
               "%32,%33,%34,%35,%36,%37,%38,%39,%40,%41,%42,%43,%44,%45,%46,%47,%48,%49,%50,%51,%52,%53,%54,%55,%56,%57,%58,%59,%60,%61,%62,%63,"
               "%64,%65,%66,%67,%68,%69,%70,%71,%72,%73,%74,%75,%76,%77,%78,%79,%80,%81,%82,%83,%84,%85,%86,%87,%88,%89,%90,%91,%92,%93,%94,%95,"
               "%96,%97,%98,%99,%100,%101,%102,%103,%104,%105,%106,%107,%108,%109,%110,%111,%112,%113,%114,%115,%116,%117,%118,%119,%120,%121,%122,%123,%124,%125,%126,%127},"
               " da, db, p, 1, 1, 0, 1;\n}\n"
               : R64(d, 0), R64(d, 64) : "r"(alo), "r"(blo), "r"(acc), "r"(DESC_HI));
}
template <int N>
__device__ __forceinline__ void fence_regs(float (&d)[N]) {
#pragma unroll
  for (int i = 0; i < N; i++) asm volatile("" : "+f"(d[i])::"memory");
}
__device__ __forceinline__ uint32_t pack_bf16(float lo, float hi) {
  uint32_t r; asm("cvt.rn.bf16x2.f32 %0, %1, %2;" : "=r"(r) : "f"(hi), "f"(lo)); return r;
}
__device__ __forceinline__ float bf16_round(float v) { return __bfloat162float(__float2bfloat16_rn(v)); }
__device__ __forceinline__ float bf_lo(uint32_t v) { return __uint_as_float(v << 16); }
__device__ __forceinline__ float bf_hi(uint32_t v) { return __uint_as_float(v & 0xFFFF0000u); }
__device__ __forceinline__ float ex2(float x) { float y; asm("ex2.approx.ftz.f32 %0, %1;" : "=f"(y) : "f"(x)); return y; }
__device__ __forceinline__ void stmatrix4(uint32_t addr, uint32_t r0, uint32_t r1, uint32_t r2, uint32_t r3) {
  asm volatile("stmatrix.sync.aligned.m8n8.x4.shared.b16 [%0], {%1,%2,%3,%4};" ::"r"(addr), "r"(r0), "r"(r1), "r"(r2), "r"(r3) : "memory");
}
__device__ __forceinline__ void ldmatrix4(uint32_t addr, uint32_t& r0, uint32_t& r1, uint32_t& r2, uint32_t& r3) {
  asm volatile("ldmatrix.sync.aligned.m8n8.x4.shared.b16 {%0,%1,%2,%3}, [%4];" : "=r"(r0), "=r"(r1), "=r"(r2), "=r"(r3) : "r"(addr) : "memory");
}
__device__ __forceinline__ void cluster_arrive() { asm volatile("barrier.cluster.arrive.relaxed;" ::: "memory"); }
__device__ __forceinline__ void cluster_wait() { asm volatile("barrier.cluster.wait;" ::: "memory"); }

__device__ __forceinline__ uint32_t read_epoch() {
  uint32_t v; asm volatile("ld.relaxed.gpu.global.u32 %0, [%1];" : "=r"(v) : "l"(&g_flags.exit_cnt) : "memory");
  return v / NCTA;
}
__device__ __forceinline__ uint32_t rnext(uint32_t r) { r += 8; return r >= NST * 8 ? (r - NST * 8) ^ 1u : r; }

#define PROF(role, slot) do { } while (0)
#define PROFC(slot) do { } while (0)

struct Cons {
  uint32_t sb;
  uint32_t bars;
  int w;
  int warp;
  int lane;
  uint32_t rank;
  uint32_t ring;
  uint32_t stphase;
  uint32_t epoch;
  uint32_t ebase;
  __device__ __forceinline__ void wait_full(uint32_t r) { mbar_wait(bars + B_FULL + (r & ~7u), r & 1u); }
  __device__ __forceinline__ uint32_t stage_addr(uint32_t r) { return sb + ((r & ~7u) << 12); }
  __device__ __forceinline__ void release(uint32_t r, uint32_t n = 1) { if (ebase) mbar_arrive_cluster(ebase + (r & ~7u), n); }
  __device__ __forceinline__ void turn_sync() { bar_sync(1 + w, 256); }
  __device__ __forceinline__ void turn_pass() { bar_arrive(2 - w, 256); }
  __device__ __forceinline__ uint32_t frag_off() {
    const int mat = lane >> 3;
    return (warp * 16 + (mat & 1) * 8 + (lane & 7)) * 128 + ((((mat >> 1) ^ lane) & 7) << 4);
  }
  template <bool SCALE>
  __device__ __forceinline__ void stage_out(const float (&a)[64], float s0, float s1) {
    mbar_wait(bars + B_STFREE + w * 8, stphase); stphase ^= 1;
    const uint32_t base = sb + SM_STG + w * 16384 + frag_off();
#pragma unroll
    for (int jj = 0; jj < 8; jj++) {
      uint32_t r0, r1, r2, r3;
      if (SCALE) {
        r0 = pack_bf16(a[8 * jj + 0] * s0, a[8 * jj + 1] * s0); r1 = pack_bf16(a[8 * jj + 2] * s1, a[8 * jj + 3] * s1);
        r2 = pack_bf16(a[8 * jj + 4] * s0, a[8 * jj + 5] * s0); r3 = pack_bf16(a[8 * jj + 6] * s1, a[8 * jj + 7] * s1);
      } else {
        r0 = pack_bf16(a[8 * jj + 0], a[8 * jj + 1]); r1 = pack_bf16(a[8 * jj + 2], a[8 * jj + 3]);
        r2 = pack_bf16(a[8 * jj + 4], a[8 * jj + 5]); r3 = pack_bf16(a[8 * jj + 6], a[8 * jj + 7]);
      }
      stmatrix4((base ^ (((2 * jj) & 7) << 4)) + (jj >> 2) * 8192, r0, r1, r2, r3);
    }
    fence_async_smem();
    bar_arrive(3 + w, 160);
  }
};

__device__ __forceinline__ void ln_row(const Params& P, int row, int lane, uint32_t epoch) {
  uint4 v[2], wr[2];
  const uint4* xr = reinterpret_cast<const uint4*>(P.x + (size_t)row * DM);
  v[0] = __ldg(xr + lane); v[1] = __ldg(xr + lane + 32);
  wr[0] = __ldg(reinterpret_cast<const uint4*>(P.w_r) + lane); wr[1] = __ldg(reinterpret_cast<const uint4*>(P.w_r) + lane + 32);
  float f[16];
#pragma unroll
  for (int c = 0; c < 2; c++) {
    const uint32_t u[4] = {v[c].x, v[c].y, v[c].z, v[c].w};
#pragma unroll
    for (int e = 0; e < 4; e++) { f[c * 8 + 2 * e] = bf_lo(u[e]); f[c * 8 + 2 * e + 1] = bf_hi(u[e]); }
  }
  float s = 0.f;
#pragma unroll
  for (int e = 0; e < 16; e++) s += f[e];
#pragma unroll
  for (int o = 16; o > 0; o >>= 1) s += __shfl_xor_sync(0xffffffffu, s, o);
  const float mean = s * (1.0f / DM);
  float q = 0.f;
#pragma unroll
  for (int e = 0; e < 16; e++) { float d = f[e] - mean; q += d * d; }
#pragma unroll
  for (int o = 16; o > 0; o >>= 1) q += __shfl_xor_sync(0xffffffffu, q, o);
  const float m = bf16_round(mean);
  const float var = bf16_round(q * (1.0f / DM));
  const float rs = 1.0f / bf16_round(sqrtf(bf16_round(var + 1e-5f)));
  float r = 0.f;
  const int g = row >> 6, rl = row & 63;
#pragma unroll
  for (int c = 0; c < 2; c++) {
    const uint32_t wu[4] = {wr[c].x, wr[c].y, wr[c].z, wr[c].w};
    uint32_t o[4];
#pragma unroll
    for (int e = 0; e < 4; e++) {
      const uint32_t d = pack_bf16(f[c * 8 + 2 * e] - m, f[c * 8 + 2 * e + 1] - m);
      o[e] = pack_bf16(bf_lo(d) * rs, bf_hi(d) * rs);
      r += bf_lo(o[e]) * bf_lo(wu[e]); r += bf_hi(o[e]) * bf_hi(wu[e]);
    }
    const int c8 = lane + 32 * c, kh = c8 >> 3, ch = c8 & 7;
    *reinterpret_cast<uint4*>(g_xn + ((size_t)(g * 8 + kh) * 64 + rl) * 128 + ((ch ^ (rl & 7)) << 4)) = make_uint4(o[0], o[1], o[2], o[3]);
  }
#pragma unroll
  for (int o = 16; o > 0; o >>= 1) r += __shfl_xor_sync(0xffffffffu, r, o);
  uint32_t u = __float_as_uint(bf16_round(r) + 0.0f);
  u = (u & 0x80000000u) ? ~u : (u | 0x80000000u);
  const unsigned long long key = ((unsigned long long)u << 32) | (unsigned long long)(0xFFFFFFFFu - (uint32_t)row);
  if (lane == 0) asm volatile("red.relaxed.gpu.global.max.u64 [%0], %1;" ::"l"(&g_flags.key[epoch & 1]), "l"(key) : "memory");
}

__device__ __forceinline__ void proj_phase(Cons& C, const Params& P) {
  uint32_t af[128];
  float acc[64];
#pragma unroll 1
  for (int ph = 0; ph < 2; ph++) {
    {
      uint32_t r = C.ring;
      if (C.w == 0) { C.wait_full(r); C.wait_full(rnext(r)); bar_arrive(8, 256); }
      else { bar_sync(8, 256); r ^= 1u; }
      const uint32_t off = C.frag_off();
#pragma unroll
      for (int st = 0; st < 2; st++) {
        C.wait_full(r);
        const uint32_t base = C.stage_addr(r) + off;
#pragma unroll
        for (int kk = 0; kk < 16; kk++)
          ldmatrix4((base ^ ((2 * (kk & 3)) << 4)) + (kk >> 2) * 8192, af[st * 64 + kk * 4], af[st * 64 + kk * 4 + 1], af[st * 64 + kk * 4 + 2],
                    af[st * 64 + kk * 4 + 3]);
        __syncwarp();
        C.release(r, 2);
        r = rnext(r);
      }
      C.ring = rnext(rnext(C.ring));
    }
    const int nt = ph ? 4 : 8;
#pragma unroll 1
    for (int t = 0; t < nt; t++) {
      uint32_t prev = 0;
      C.turn_sync();
#pragma unroll
      for (int c = 0; c < 4; c++) {
        C.wait_full(C.ring);
        const uint32_t blo = desc_lo(C.stage_addr(C.ring), 16384);
        WG_FENCE();
#pragma unroll
        for (int kk = 0; kk < 8; kk++)
          mma_rs128<1>(acc, af[c * 32 + kk * 4], af[c * 32 + kk * 4 + 1], af[c * 32 + kk * 4 + 2], af[c * 32 + kk * 4 + 3], blo + kk * 128,
                       (c | kk) != 0);
        WG_COMMIT();
        if (c == 3) C.turn_pass();
        if (c > 0) { WG_WAIT(1); C.release(prev); }
        prev = C.ring;
        C.ring = rnext(C.ring);
      }
      if (t == 0) C.ring = rnext(rnext(C.ring));
      WG_WAIT(0);
      C.release(prev);
      fence_regs(acc);
      C.stage_out<false>(acc, 1.0f, 1.0f);
      PROFC(ph * 8 + t);
      if (ph == 0) {
        if (t == 0) C.epoch = read_epoch();
        if (t == 1 || t == 2) ln_row(P, blockIdx.x * 16 + (C.w * 4 + C.warp) * 2 + t - 1, C.lane, C.epoch);
      }
    }
  }
}

__device__ __forceinline__ void att_phase(Cons& C, const int a) {
  constexpr float SC = 0.08838834764831845f * 1.4426950408889634f;
  float s[64], o[64];
  uint32_t q[32], p[32];
#pragma unroll
  for (int i = 0; i < 64; i++) o[i] = 0.f;
#pragma unroll
  for (int i = 0; i < 32; i++) p[i] = 0u;
  const uint32_t qoff = C.w * 16384 + C.frag_off();
  auto load_q = [&](uint32_t r) {
    C.wait_full(r);
    const uint32_t base = C.stage_addr(r) + qoff;
#pragma unroll
    for (int kk = 0; kk < 8; kk++) ldmatrix4((base ^ ((2 * (kk & 3)) << 4)) + (kk >> 2) * 8192, q[4 * kk], q[4 * kk + 1], q[4 * kk + 2], q[4 * kk + 3]);
    __syncwarp();
    C.release(r);
  };
  uint32_t ring = C.ring, qr = ring, kr, vr = 0;
  load_q(qr);
  ring = rnext(ring);
  kr = ring; ring = rnext(ring);
  C.wait_full(kr);
  const int sw = a + 1 - C.w;
  float mc0 = 0.f, mc1 = 0.f, l0 = 1.f, l1 = 1.f, a0 = 1.f, a1 = 1.f;
  int th0 = 0, th1 = 0;
  int st = 0, gs = 0, pvacc = 0;
  auto step = [&](auto fast_tag) {
    constexpr bool FAST = decltype(fast_tag)::value;
    const uint32_t klo = desc_lo(C.stage_addr(kr), 16), vlo = desc_lo(C.stage_addr(vr), 16384);
    C.turn_sync();
    WG_FENCE();
#pragma unroll
    for (int kk = 0; kk < 8; kk++)
      mma_rs128<0>(s, q[4 * kk], q[4 * kk + 1], q[4 * kk + 2], q[4 * kk + 3], klo + (((kk >> 2) * 16384 + (kk & 3) * 32) >> 4), kk != 0);
    WG_COMMIT();
    if (FAST || gs > 0) {
      if (!FAST) WG_FENCE();
#pragma unroll
      for (int kk = 0; kk < 8; kk++) mma_rs128<1>(o, p[4 * kk], p[4 * kk + 1], p[4 * kk + 2], p[4 * kk + 3], vlo + kk * 128, kk ? 1 : pvacc);
      WG_COMMIT();
    } else {
      WG_COMMIT();
    }
    C.turn_pass();
    const uint32_t ck = kr, cv = vr;
    const bool first = !FAST && (st == 0 || st == sw), last = !FAST && gs == 33;
    const int ns = (!FAST && st == 16) ? 0 : st + 1;
    if (FAST) {
      kr = ring; vr = rnext(kr); ring = rnext(vr);
    } else {
      if (ns == a || (ns == 0 && !last)) { qr = ring; ring = rnext(ring); }
      if (!last) {
        kr = ring; ring = rnext(ring);
        if (ns == a) { if (C.w) kr = ring; ring = rnext(ring); }
      }
      vr = ring; ring = rnext(ring);
      if (ns == a + 1) { if (C.w) vr = ring; ring = rnext(ring); }
      if (last) kr = vr;
      if (first) {
        l0 += __shfl_xor_sync(0xffffffffu, l0, 1); l1 += __shfl_xor_sync(0xffffffffu, l1, 1);
        l0 += __shfl_xor_sync(0xffffffffu, l0, 2); l1 += __shfl_xor_sync(0xffffffffu, l1, 2);
        a0 = __fdividef(1.0f, l0); a1 = __fdividef(1.0f, l1);
        l0 = 0.f; l1 = 0.f; mc0 = -INFINITY; mc1 = -INFINITY; th0 = INT_MIN; th1 = INT_MIN;
      }
    }
    WG_WAIT(1);
    C.release(ck, (!FAST && st == a) ? 2 : 1);
    if (!FAST && (ns == sw || (ns == 0 && !last))) load_q(qr);
    fence_regs(s);
    if (!FAST && (st == sw - 1 || st == sw)) {
      const int odd = (int)C.rank ^ C.w ^ (st == sw ? 0 : 1);
      const int lim0 = odd * 64 + C.warp * 16 + (C.lane >> 2) - 2 * (C.lane & 3);
      const int lim1 = lim0 + 8;
#pragma unroll
      for (int i = 0; i < 16; i++) {
        if (8 * i > lim0) s[4 * i] = -INFINITY;
        if (8 * i + 1 > lim0) s[4 * i + 1] = -INFINITY;
        if (8 * i > lim1) s[4 * i + 2] = -INFINITY;
        if (8 * i + 1 > lim1) s[4 * i + 3] = -INFINITY;
      }
    }
    bool resc = first;
    if (!first) {
      int u0[2], u1[2];
#pragma unroll
      for (int i = 0; i < 2; i++) {
        u0[i] = max(__float_as_int(s[4 * i]), __float_as_int(s[4 * i + 1]));
        u1[i] = max(__float_as_int(s[4 * i + 2]), __float_as_int(s[4 * i + 3]));
      }
#pragma unroll
      for (int i = 2; i < 16; i++) {
        u0[i & 1] = max(max(u0[i & 1], __float_as_int(s[4 * i])), __float_as_int(s[4 * i + 1]));
        u1[i & 1] = max(max(u1[i & 1], __float_as_int(s[4 * i + 2])), __float_as_int(s[4 * i + 3]));
      }
      resc = __any_sync(0xffffffffu, max(u0[0], u0[1]) >= th0 || max(u1[0], u1[1]) >= th1);
    }
    if (__builtin_expect(resc, !FAST)) {
      float n0 = fmaxf(s[0], s[1]), n1 = fmaxf(s[2], s[3]);
#pragma unroll
      for (int i = 1; i < 16; i++) { n0 = fmaxf(n0, fmaxf(s[4 * i], s[4 * i + 1])); n1 = fmaxf(n1, fmaxf(s[4 * i + 2], s[4 * i + 3])); }
      n0 = fmaxf(n0, __shfl_xor_sync(0xffffffffu, n0, 1)); n1 = fmaxf(n1, __shfl_xor_sync(0xffffffffu, n1, 1));
      n0 = fmaxf(n0, __shfl_xor_sync(0xffffffffu, n0, 2)); n1 = fmaxf(n1, __shfl_xor_sync(0xffffffffu, n1, 2));
      n0 = fmaxf(n0 * SC, mc0); n1 = fmaxf(n1 * SC, mc1);
      const float f0 = ex2(mc0 - n0), f1 = ex2(mc1 - n1);
      l0 *= f0; l1 *= f1; mc0 = n0; mc1 = n1;
      if (!first) { a0 = f0; a1 = f1; }
      th0 = __float_as_int((n0 + 8.0f) * (1.0f / SC)); th1 = __float_as_int((n1 + 8.0f) * (1.0f / SC));
      th0 = th0 < 0 ? INT_MIN : th0; th1 = th1 < 0 ? INT_MIN : th1;
    }
    const uint32_t ready = mbar_test2(C.bars + B_FULL + (kr & ~7u), kr & 1u, C.bars + B_FULL + (vr & ~7u), vr & 1u);
#pragma unroll
    for (int i = 0; i < 8; i++) {
      s[4 * i] = ex2(fmaf(s[4 * i], SC, -mc0)); s[4 * i + 1] = ex2(fmaf(s[4 * i + 1], SC, -mc0));
      s[4 * i + 2] = ex2(fmaf(s[4 * i + 2], SC, -mc1)); s[4 * i + 3] = ex2(fmaf(s[4 * i + 3], SC, -mc1));
      l0 += s[4 * i] + s[4 * i + 1]; l1 += s[4 * i + 2] + s[4 * i + 3];
    }
#pragma unroll
    for (int i = 0; i < 32; i++) asm volatile("" : "+f"(s[i])::"memory");
    asm volatile("" : "+f"(l0), "+f"(l1)::"memory");
    if (__builtin_expect(!ready, 0)) { C.wait_full(kr); C.wait_full(vr); }
    WG_WAIT(0);
    fence_regs(o);
    if (FAST || gs > 0) {
      C.release(cv, (!FAST && st == a + 1) ? 2 : 1);
      if (first) {
        C.stage_out<true>(o, a0, a1);
      } else if (__builtin_expect(resc, 0)) {
#pragma unroll
        for (int i = 0; i < 16; i++) { o[4 * i] *= a0; o[4 * i + 1] *= a0; o[4 * i + 2] *= a1; o[4 * i + 3] *= a1; }
      }
    }
#pragma unroll
    for (int i = 0; i < 8; i++) {
      const int n = 32 + 4 * i;
      s[n] = ex2(fmaf(s[n], SC, -mc0)); s[n + 1] = ex2(fmaf(s[n + 1], SC, -mc0));
      s[n + 2] = ex2(fmaf(s[n + 2], SC, -mc1)); s[n + 3] = ex2(fmaf(s[n + 3], SC, -mc1));
      l0 += s[n] + s[n + 1]; l1 += s[n + 2] + s[n + 3];
      p[2 * i] = pack_bf16(s[4 * i], s[4 * i + 1]); p[2 * i + 1] = pack_bf16(s[4 * i + 2], s[4 * i + 3]);
      p[16 + 2 * i] = pack_bf16(s[n], s[n + 1]); p[17 + 2 * i] = pack_bf16(s[n + 2], s[n + 3]);
    }
    pvacc = first ? 0 : 1;
    st = ns;
    PROFC(13 + gs);
    gs++;
  };
  const uint32_t special = 1u | (7u << (a - 1)) | (1u << 16);
  PROFC(12);
#pragma unroll 1
  while (gs < 34) {
    step(std::false_type());
#pragma unroll 1
    while (!((special >> st) & 1u)) step(std::true_type());
  }
  {
    const uint32_t vlo = desc_lo(C.stage_addr(vr), 16384);
    C.turn_sync();
    WG_FENCE();
#pragma unroll
    for (int kk = 0; kk < 8; kk++) mma_rs128<1>(o, p[4 * kk], p[4 * kk + 1], p[4 * kk + 2], p[4 * kk + 3], vlo + kk * 128, kk ? 1 : pvacc);
    WG_COMMIT();
    if (C.w == 0) C.turn_pass();
    l0 += __shfl_xor_sync(0xffffffffu, l0, 1); l1 += __shfl_xor_sync(0xffffffffu, l1, 1);
    l0 += __shfl_xor_sync(0xffffffffu, l0, 2); l1 += __shfl_xor_sync(0xffffffffu, l1, 2);
    a0 = __fdividef(1.0f, l0); a1 = __fdividef(1.0f, l1);
    WG_WAIT(0);
    C.release(vr);
    fence_regs(o);
    C.stage_out<true>(o, a0, a1);
    PROFC(47);
  }
  C.ring = ring;
}

__device__ __forceinline__ void op_phase(Cons& C, const Params& P, int j, int nh, int ks) {
  float acc[128];
#pragma unroll
  for (int i = 0; i < 128; i++) acc[i] = 0.f;
  uint32_t pa = 0, pb = 0;
#pragma unroll 1
  for (int t = 0; t < 8; t++) {
    const uint32_t ia = C.ring, i0 = rnext(ia), i1 = rnext(i0);
    C.ring = rnext(i1);
    C.wait_full(ia);
    const uint32_t alo = desc_lo(C.stage_addr(ia) + C.w * 16384, 16);
    C.wait_full(i0);
    const uint32_t b0 = desc_lo(C.stage_addr(i0), 8192);
    WG_FENCE();
#pragma unroll
    for (int kk = 0; kk < 4; kk++) mma_ss256(acc, alo + kk * 2, b0 + kk * 128, 1);
    WG_COMMIT();
    if (t > 0) { WG_WAIT(1); if (t < 7) { C.release(pa); C.release(pb); } }
    C.wait_full(i1);
    const uint32_t b1 = desc_lo(C.stage_addr(i1), 8192);
    WG_FENCE();
#pragma unroll
    for (int kk = 0; kk < 4; kk++) mma_ss256(acc, alo + 512 + kk * 2, b1 + kk * 128, 1);
    WG_COMMIT();
    WG_WAIT(1);
    if (t < 6) C.release(i0);
    pa = ia; pb = i1;
  }
  cluster_arrive();
  const int tid = C.warp * 32 + C.lane;
  const int g = 4 * j + 2 * (int)C.rank + C.w;
  const int kh = 4 * nh + ks;
  uint4 xv[4], nv[4];
#pragma unroll
  for (int i = 0; i < 4; i++) {
    const int idx = C.warp * 128 + C.lane + 32 * i, row = idx >> 3, ch = (idx ^ row) & 7;
    xv[i] = __ldg(reinterpret_cast<const uint4*>(P.x + (size_t)(g * 64 + row) * DM + kh * 64 + ch * 8));
    nv[i] = __ldcg(reinterpret_cast<const uint4*>(g_xn + (size_t)(g * 8 + kh) * 8192) + idx);
  }
  const unsigned long long key = __ldcg(&g_flags.key[C.epoch & 1]);
  WG_WAIT(0);
  fence_regs(acc);
  PROFC(48);
  const int tile = j * 2 + nh, sub = (int)C.rank * 2 + C.w;
#pragma unroll
  for (int pp = 1; pp < 4; pp++) {
    uint4* dst = g_exch + (size_t)(((tile * 4 + ((pp + ks) & 3)) * 3 + (pp - 1)) * 4 + sub) * 512 + tid;
#pragma unroll
    for (int v = 0; v < 4; v++) {
      const float* f = acc + 32 * pp + 8 * v;
      __stcg(dst + v * 128, make_uint4(pack_bf16(f[0], f[1]), pack_bf16(f[2], f[3]), pack_bf16(f[4], f[5]), pack_bf16(f[6], f[7])));
    }
  }
  __syncwarp();
  if (C.lane < 3) {
    fence_gpu();
    red_relaxed(&g_flags.ex_done[((tile * 4 + ((C.lane + 1 + ks) & 3)) * 4 + sub) * 4 + C.warp], 1);
  }
  PROFC(49);
  mbar_wait(C.bars + B_STFREE + C.w * 8, C.stphase);
  if (C.lane == 0) flag_wait(&g_flags.ex_done[((tile * 4 + ks) * 4 + sub) * 4 + C.warp], (C.epoch + 1) * 3);
  __syncwarp();
  PROFC(50);
#pragma unroll
  for (int pp = 1; pp < 4; pp++) {
    const uint4* src = g_exch + (size_t)(((tile * 4 + ks) * 3 + (pp - 1)) * 4 + sub) * 512 + tid;
#pragma unroll
    for (int v = 0; v < 4; v++) {
      const uint4 f = __ldcg(src + v * 128);
      float* d = acc + 8 * v;
      d[0] += bf_lo(f.x); d[1] += bf_hi(f.x); d[2] += bf_lo(f.y); d[3] += bf_hi(f.y);
      d[4] += bf_lo(f.z); d[5] += bf_hi(f.z); d[6] += bf_lo(f.w); d[7] += bf_hi(f.w);
    }
  }
  const uint32_t stg = C.sb + SM_STG + C.w * 16384;
  {
    const uint32_t base = stg + C.frag_off();
#pragma unroll
    for (int jj = 0; jj < 4; jj++)
      stmatrix4(base ^ ((2 * jj) << 4), pack_bf16(acc[8 * jj], acc[8 * jj + 1]), pack_bf16(acc[8 * jj + 2], acc[8 * jj + 3]),
                pack_bf16(acc[8 * jj + 4], acc[8 * jj + 5]), pack_bf16(acc[8 * jj + 6], acc[8 * jj + 7]));
  }
  __syncwarp();
  const int sel = (int)(0xFFFFFFFFu - (uint32_t)key);
#pragma unroll
  for (int i = 0; i < 4; i++) {
    const int idx = C.warp * 128 + C.lane + 32 * i, row = idx >> 3, ch = (idx ^ row) & 7;
    uint4 av;
    asm volatile("ld.shared.v4.u32 {%0,%1,%2,%3}, [%4];" : "=r"(av.x), "=r"(av.y), "=r"(av.z), "=r"(av.w) : "r"(stg + idx * 16) : "memory");
    const uint32_t au[4] = {av.x, av.y, av.z, av.w}, xu[4] = {xv[i].x, xv[i].y, xv[i].z, xv[i].w};
    uint32_t nu[4] = {nv[i].x, nv[i].y, nv[i].z, nv[i].w};
    if (g * 64 + row == sel) {
      flag_wait(&g_flags.moe_done, (C.epoch + 1) * 4);
      uint32_t ub = (uint32_t)(key >> 32);
      ub = (ub & 0x80000000u) ? (ub & 0x7FFFFFFFu) : ~ub;
      const float sig = bf16_round(1.0f / (1.0f + expf(-__uint_as_float(ub))));
#pragma unroll
      for (int e = 0; e < 4; e++) {
        const int col = kh * 64 + ch * 8 + 2 * e;
        float y0 = 0.f, y1 = 0.f;
#pragma unroll
        for (int c = 0; c < 4; c++) { y0 += __ldcg(&g_ypart[c * DM + col]); y1 += __ldcg(&g_ypart[c * DM + col + 1]); }
        y0 = bf16_round(bf16_round(y0) * sig); y1 = bf16_round(bf16_round(y1) * sig);
        nu[e] = pack_bf16(bf_lo(nu[e]) + y0, bf_hi(nu[e]) + y1);
      }
    }
    uint32_t ou[4];
#pragma unroll
    for (int e = 0; e < 4; e++)
      ou[e] = pack_bf16(bf16_round(bf_lo(xu[e]) + bf_lo(au[e])) + bf_lo(nu[e]), bf16_round(bf_hi(xu[e]) + bf_hi(au[e])) + bf_hi(nu[e]));
    *reinterpret_cast<uint4*>(P.out + (size_t)(g * 64 + row) * DM + kh * 64 + ch * 8) = make_uint4(ou[0], ou[1], ou[2], ou[3]);
  }
  PROFC(51);
}

__device__ __forceinline__ void moe_phase(Cons& C, const Params& P, int part, unsigned char* smem) {
  const int tid = C.w * 128 + C.warp * 32 + C.lane;
  float* xs = reinterpret_cast<float*>(smem + SM_STG);
  float* hs = xs + 512;
  float* red = xs + 1024;
  if (tid == 0) flag_wait(&g_flags.ln_done, (C.epoch + 1) * 256);
  bar_sync(5, 256);
  const unsigned long long key = __ldcg(&g_flags.key[C.epoch & 1]);
  const int sel = (int)(0xFFFFFFFFu - (uint32_t)key);
  {
    const int g = sel >> 6, rl = sel & 63;
    const int c2 = tid * 2, kh = c2 >> 6, ch = (c2 >> 3) & 7;
    const uint32_t u = __ldcg(reinterpret_cast<const uint32_t*>(g_xn + ((size_t)(g * 8 + kh) * 64 + rl) * 128 + ((ch ^ (rl & 7)) << 4) + (c2 & 7) * 2));
    xs[c2] = bf_lo(u); xs[c2 + 1] = bf_hi(u);
  }
  bar_sync(5, 256);
  if (tid < 224) {
    const int chunk = tid % 56, kg = tid / 56;
    const uint4* wg = reinterpret_cast<const uint4*>(P.w_gate + (size_t)kg * 128 * FF + part * 448 + chunk * 8);
    const uint4* wu = reinterpret_cast<const uint4*>(P.w_up + (size_t)kg * 128 * FF + part * 448 + chunk * 8);
    float ag[8], au[8];
#pragma unroll
    for (int e = 0; e < 8; e++) { ag[e] = 0.f; au[e] = 0.f; }
#pragma unroll 1
    for (int k0 = 0; k0 < 128; k0 += 16) {
      uint4 vg[16], vu[16];
#pragma unroll
      for (int i = 0; i < 16; i++) { vg[i] = __ldg(wg + (size_t)(k0 + i) * (FF / 8)); vu[i] = __ldg(wu + (size_t)(k0 + i) * (FF / 8)); }
#pragma unroll
      for (int i = 0; i < 16; i++) {
        const float xk = xs[kg * 128 + k0 + i];
        const uint32_t a[4] = {vg[i].x, vg[i].y, vg[i].z, vg[i].w}, b[4] = {vu[i].x, vu[i].y, vu[i].z, vu[i].w};
#pragma unroll
        for (int e = 0; e < 4; e++) {
          ag[2 * e] += xk * bf_lo(a[e]); ag[2 * e + 1] += xk * bf_hi(a[e]);
          au[2 * e] += xk * bf_lo(b[e]); au[2 * e + 1] += xk * bf_hi(b[e]);
        }
      }
    }
#pragma unroll
    for (int e = 0; e < 8; e++) { red[(kg * 2) * 448 + chunk * 8 + e] = ag[e]; red[(kg * 2 + 1) * 448 + chunk * 8 + e] = au[e]; }
  }
  bar_sync(5, 256);
  for (int f = tid; f < 448; f += 256) {
    float gs = 0.f, us = 0.f;
#pragma unroll
    for (int kg = 0; kg < 4; kg++) { gs += red[(kg * 2) * 448 + f]; us += red[(kg * 2 + 1) * 448 + f]; }
    gs = bf16_round(gs); us = bf16_round(us);
    const float sl = bf16_round(gs / (1.0f + expf(-gs)));
    hs[f] = bf16_round(sl * us);
  }
  bar_sync(5, 256);
  {
    const int chunk = tid & 63, rg = tid >> 6;
    const uint4* wd = reinterpret_cast<const uint4*>(P.w_down + (size_t)(part * 448 + rg * 112) * DM + chunk * 8);
    float ay[8];
#pragma unroll
    for (int e = 0; e < 8; e++) ay[e] = 0.f;
#pragma unroll 1
    for (int k0 = 0; k0 < 112; k0 += 28) {
      uint4 v[28];
#pragma unroll
      for (int i = 0; i < 28; i++) v[i] = __ldg(wd + (size_t)(k0 + i) * (DM / 8));
#pragma unroll
      for (int i = 0; i < 28; i++) {
        const float hk = hs[rg * 112 + k0 + i];
        const uint32_t a[4] = {v[i].x, v[i].y, v[i].z, v[i].w};
#pragma unroll
        for (int e = 0; e < 4; e++) { ay[2 * e] += hk * bf_lo(a[e]); ay[2 * e + 1] += hk * bf_hi(a[e]); }
      }
    }
#pragma unroll
    for (int e = 0; e < 8; e++) red[rg * 512 + chunk * 8 + e] = ay[e];
  }
  bar_sync(5, 256);
  for (int c = tid; c < DM; c += 256) g_ypart[part * DM + c] = red[c] + red[512 + c] + red[1024 + c] + red[1536 + c];
  bar_sync(5, 256);
  if (tid == 0) red_release(&g_flags.moe_done, 1);
}

__device__ __forceinline__ int proj_head(int t, int cg) {
  if (t < 8) return (t < 4 ? 16 : 0) + 2 * cg + ((t >> 1) & 1);
  return (t < 10 ? 0 : 16) + 2 * cg + (t & 1);
}

__global__ void __launch_bounds__(384, 1) mega_kernel(const __grid_constant__ Params P) {
  extern __shared__ unsigned char smem_raw[];
  const uint32_t sraw = smem_u32(smem_raw);
  const uint32_t sb = (sraw + 1023u) & ~1023u;
  const uint32_t bars = sb + SM_BAR;
  const int warp_id = __shfl_sync(0xffffffffu, threadIdx.x >> 5, 0);
  const int lane = threadIdx.x & 31;
  uint32_t rank; asm volatile("mov.u32 %0, %%cluster_ctarank;" : "=r"(rank));
  const int pair = blockIdx.x >> 1;
  const bool spare = pair >= 64;
  const int jx = (pair & 3) + (pair & 4);
  const int a = 2 * jx + 1;

  if (threadIdx.x == 0) {
    for (int s = 0; s < NST; s++) { mbar_init(bars + B_FULL + s * 8, 1); mbar_init(bars + B_EMPTY + s * 8, 16); }
    mbar_init(bars + B_STFREE, 1); mbar_init(bars + B_STFREE + 8, 1);
    mbar_init(bars + B_DONE, 11);
    asm volatile("fence.mbarrier_init.release.cluster;" ::: "memory");
  }
  __syncthreads();
  asm volatile("barrier.cluster.arrive.relaxed.aligned;\nbarrier.cluster.wait.aligned;" ::: "memory");

  if (warp_id < 4) {
    asm volatile("setmaxnreg.dec.sync.aligned.u32 40;");
    if (warp_id == 0) {
      if (spare) {
        __nanosleep(4000);
        const int part = (pair - 64) * 2 + (int)rank;
        for (int i = lane; i < 512; i += 32) {
          l2_prefetch(P.w_gate + (size_t)i * FF + part * 448, 896);
          l2_prefetch(P.w_up + (size_t)i * FF + part * 448, 896);
        }
        if (lane < 28) l2_prefetch(P.w_down + (size_t)(part * 448 + lane * 16) * DM, 16384);
        if (blockIdx.x == 128 && lane == 0) g_flags.key[(read_epoch() + 1) & 1] = 0;
      } else {
        uint32_t ring = 1, fb = 0, epoch = 0;
        auto acquire = [&]() -> uint32_t {
          mbar_wait(bars + B_EMPTY + (ring & ~7u), ring & 1u);
          fb = bars + B_FULL + (ring & ~7u);
          mbar_expect_tx(fb, STAGE);
          const uint32_t dst = sb + ((ring & ~7u) << 12);
          ring = rnext(ring);
          return dst;
        };
        if (lane == 0) {
          PROF(2, 0);
          const int cg = pair >> 3, g0 = ((pair & 7) * 2 + (int)rank) * 2;
#pragma unroll 1
          for (int t = 0; t < 12; t++) {
#pragma unroll 1
            for (int w = 0; w < 2; w++) {
              if (t == 0) {
                for (int st = 0; st < 2; st++) {
                  const uint32_t dst = acquire();
                  for (int kh = 0; kh < 4; kh++) tma_load(dst + kh * 8192, &P.tm_ckv, (st * 4 + kh) * 64, (g0 + w) * 64, fb);
                }
              } else if (t == 8) {
                if (w == 0) { flag_wait(&g_flags.ln_done, (epoch + 1) * 256); fence_async_global(); PROF(2, 1); }
                for (int st = 0; st < 2; st++) {
                  const uint32_t dst = acquire();
                  bulk_load(dst, g_xn + (size_t)((g0 + w) * 8 + st * 4) * 8192, 32768, fb);
                }
              }
              if (w == 0) {
                const CUtensorMap* tw = t >= 8 ? &P.tm_wq : ((t & 1) ? &P.tm_wuv : &P.tm_wuk);
                const int col = proj_head(t, cg) * 128 + rank * 64;
                for (int c = 0; c < 4; c++) {
                  const uint32_t dst = acquire();
                  tma_load_mc(dst + rank * 16384, tw, col, c * 128, fb);
                }
                if (t == 0) { l2_prefetch(P.x + (size_t)blockIdx.x * 16 * DM, 16384); epoch = read_epoch(); }
              }
            }
          }
          const int h0 = pair >> 2;
          flag_wait(&g_flags.kv_done[h0], (epoch + 1) * 64);
          flag_wait(&g_flags.q_done[h0], (epoch + 1) * 32);
          fence_async_global();
          PROF(2, 2);
          const unsigned char* kb = g_kv + (size_t)h0 * 2 * 16 * 32768 + rank * 16384;
          auto kv_load = [&](const unsigned char* src) {
            const uint32_t dst = acquire();
            bulk_load_mc(dst + rank * 16384, src, 16384, fb);
          };
#pragma unroll 1
          for (int rd = 0; rd < 2; rd++) {
            const int h = h0 + 16 * rd;
            const unsigned char* vb = kb + 16 * 32768;
#pragma unroll 1
            for (int s = 0; s < 17; s++) {
              if (s == 0 || s == a) {
                const int jj = s == 0 ? jx : 7 - jx;
                const int gL = 4 * jj + 3 - (int)rank, gS = 4 * jj + (int)rank;
                const uint32_t dst = acquire();
                bulk_load(dst, g_qc + ((size_t)(s == 0 ? gL : gS) * 32 + h) * 16384, 16384, fb);
                bulk_load(dst + 16384, g_qc + ((size_t)(s == 0 ? gS : gL) * 32 + h) * 16384, 16384, fb);
              }
              if (s <= a) kv_load(kb + (size_t)s * 32768);
              if (s >= a) kv_load(kb + (size_t)(16 - s) * 32768);
              if (s == 0) {
                if (rd) kv_load(vb - (size_t)16 * 2 * 16 * 32768);
              } else {
                if (s - 1 <= a) kv_load(vb + (size_t)(s - 1) * 32768);
                if (s - 1 >= a) kv_load(vb + (size_t)(17 - s) * 32768);
              }
              if (rd == 0 && s == 8) {
                flag_wait(&g_flags.kv_done[h0 + 16], (epoch + 1) * 64);
                flag_wait(&g_flags.q_done[h0 + 16], (epoch + 1) * 32);
                fence_async_global();
                PROF(2, 3);
              }
            }
            if (rd) kv_load(vb);
            kb += (size_t)16 * 2 * 16 * 32768;
          }
        }
        epoch = __shfl_sync(0xffffffffu, epoch, 0);
        const int j = pair >> 3, nh = (pair >> 2) & 1, ks = pair & 3;
        auto op_head = [&](int t) { return t < 4 ? ks * 4 + t : 16 + 4 * ks + 2 * (t & 1) + (((j >> 2) ^ (t >> 1)) & 1); };
        int done = 0;
        while (done < 8) {
          const bool ok = lane >= 8 || flag_ok(&g_flags.ctx_done[j * 32 + op_head(lane & 7)], (epoch + 1) * 4);
          const unsigned miss = ~__ballot_sync(0xffffffffu, ok);
          const int upto = miss ? __ffs(miss) - 1 : 8;
          __syncwarp();
          if (upto > done) {
            if (lane == 0) {
              fence_async_global();
              PROF(2, 4 + done);
              for (int t = done; t < upto; t++) {
                const int hh = op_head(t);
                uint32_t dst = acquire();
                const unsigned char* src = g_qc + ((size_t)(4 * j + 2 * rank) * 32 + hh) * 16384;
                bulk_load(dst, src, 16384, fb);
                bulk_load(dst + 16384, src + (size_t)32 * 16384, 16384, fb);
                for (int bb = 0; bb < 2; bb++) {
                  dst = acquire();
                  tma_load_mc(dst + rank * 16384, &P.tm_wo, nh * 256 + ((2 * rank + ks) & 3) * 64, hh * 128 + bb * 64, fb);
                  tma_load_mc(dst + rank * 16384 + 8192, &P.tm_wo, nh * 256 + ((2 * rank + 1 + ks) & 3) * 64, hh * 128 + bb * 64, fb);
                }
              }
            }
            __syncwarp();
            done = upto;
          } else {
            __nanosleep(100);
          }
        }
      }
      if (lane == 0) mbar_arrive(bars + B_DONE);
    } else if (warp_id < 3) {
      const int w = warp_id - 1;
      const uint32_t stg = sb + SM_STG + w * 16384;
      if (!spare) {
        const int cg = pair >> 3, rb = (pair & 7) * 2 + (int)rank;
        __nanosleep(400);
        l2_prefetch((w ? P.w_uv : P.w_uk) + (size_t)(rb * 32 + lane) * 4096 + 2048 + cg * 256, 512);
#pragma unroll 1
        for (int t = 0; t < 16; t++) {
          unsigned char* dst;
          unsigned* flag;
          uint32_t half = 8192;
          if (t < 8) {
            const int h = proj_head(t, cg);
            dst = g_kv + ((size_t)(h * 2 + (t & 1)) * 16 + rb) * 32768 + w * 8192; half = 16384;
            flag = &g_flags.kv_done[h];
          } else if (t < 12) {
            const int h = proj_head(t, cg);
            dst = g_qc + ((size_t)(rb * 2 + w) * 32 + h) * 16384;
            flag = &g_flags.q_done[h];
          } else {
            const int h = (pair >> 2) + 16 * ((t >> 1) & 1), y = t & 1;
            const int jj = y ? 7 - jx : jx;
            const int g = 4 * jj + ((y == w) ? 3 - (int)rank : (int)rank);
            dst = g_qc + ((size_t)g * 32 + h) * 16384;
            flag = &g_flags.ctx_done[jj * 32 + h];
          }
          bar_sync(3 + w, 160);
          if (lane == 0) {
            bulk_store(dst, stg, 8192);
            bulk_store(dst + half, stg + 8192, 8192);
            bulk_commit();
            bulk_wait_read0();
            mbar_arrive(bars + B_STFREE + w * 8);
            bulk_wait0();
            fence_gpu();
            red_relaxed(flag, 1);
            if (t == 3) red_relaxed(&g_flags.ln_done, 1);
          }
          __syncwarp();
          if (t == 0) l2_prefetch((w ? P.w_uv : P.w_uk) + (size_t)(rb * 32 + lane) * 4096 + cg * 256, 512);
          if (t == 3) l2_prefetch(P.w_q + (size_t)(rb * 32 + lane) * 4096 + w * 2048 + cg * 256, 512);
          if (t == 14) l2_prefetch(P.w_o + (size_t)(blockIdx.x * 64 + w * 32 + lane) * 256, 512);
        }
      }
      if (lane == 0) mbar_arrive(bars + B_DONE);
    } else {
      if (lane == 0) {
        uint32_t t0 = clk32();
        while (!mbar_try(bars + B_DONE, 0)) { __nanosleep(100); if (clk32() - t0 > TIMEOUT_CLKS) __trap(); }
        red_relaxed(&g_flags.exit_cnt, 1);
      }
      __syncwarp();
    }
    cluster_arrive();
    cluster_wait();
  } else {
    asm volatile("setmaxnreg.inc.sync.aligned.u32 232;");
    Cons C;
    C.sb = sb; C.bars = bars; C.w = (warp_id - 4) >> 2; C.warp = warp_id & 3; C.lane = lane; C.rank = rank;
    C.ring = 0; C.stphase = 1; C.epoch = 0;
    C.ebase = mapa(bars + B_EMPTY, lane & 1);
    if (lane >= 2) C.ebase = 0;
    asm volatile("" : "+r"(C.ebase));
    PROFC(62);
    if (spare) {
      cluster_arrive();
      C.epoch = read_epoch();
      moe_phase(C, P, (pair - 64) * 2 + (int)rank, smem_raw + (sb - sraw));
    } else {
      if (C.w == 1) bar_arrive(1, 256);
      proj_phase(C, P);
      att_phase(C, a);
      op_phase(C, P, pair >> 3, (pair >> 2) & 1, pair & 3);
    }
    __syncwarp();
    if (lane == 0) mbar_arrive(bars + B_DONE);
    cluster_wait();
  }
}

typedef CUresult (*EncodeFn)(CUtensorMap*, CUtensorMapDataType, cuuint32_t, void*, const cuuint64_t*, const cuuint64_t*, const cuuint32_t*,
                             const cuuint32_t*, CUtensorMapInterleave, CUtensorMapSwizzle, CUtensorMapL2promotion, CUtensorMapFloatOOBfill);

void make_map(EncodeFn enc, CUtensorMap* tm, const void* ptr, int cols, int rows, int box_rows) {
  cuuint64_t dims[2] = {(cuuint64_t)cols, (cuuint64_t)rows};
  cuuint64_t strides[1] = {(cuuint64_t)cols * 2};
  cuuint32_t box[2] = {64, (cuuint32_t)box_rows};
  cuuint32_t es[2] = {1, 1};
  enc(tm, CU_TENSOR_MAP_DATA_TYPE_BFLOAT16, 2, const_cast<void*>(ptr), dims, strides, box, es, CU_TENSOR_MAP_INTERLEAVE_NONE,
      CU_TENSOR_MAP_SWIZZLE_128B, CU_TENSOR_MAP_L2_PROMOTION_L2_256B, CU_TENSOR_MAP_FLOAT_OOB_FILL_NONE);
}

}

extern "C" void kernel_launch(void* const* d_in, const int* in_sizes, int n_in, void* d_out, int out_size) {
  (void)in_sizes; (void)n_in; (void)out_size;
  static EncodeFn enc = nullptr;
  if (!enc) {
    void* fn = nullptr;
    cudaDriverEntryPointQueryResult qr;
    cudaGetDriverEntryPoint("cuTensorMapEncodeTiled", &fn, cudaEnableDefault, &qr);
    enc = (EncodeFn)fn;
    cudaFuncSetAttribute(mega_kernel, cudaFuncAttributeMaxDynamicSharedMemorySize, SMEM_BYTES);
  }
  Params P;
  make_map(enc, &P.tm_ckv, d_in[1], 512, 2048, 64);
  make_map(enc, &P.tm_wq, d_in[2], 4096, 512, 128);
  make_map(enc, &P.tm_wuk, d_in[3], 4096, 512, 128);
  make_map(enc, &P.tm_wuv, d_in[4], 4096, 512, 128);
  make_map(enc, &P.tm_wo, d_in[5], 512, 4096, 64);
  P.x = (const __nv_bfloat16*)d_in[0];
  P.w_q = (const __nv_bfloat16*)d_in[2];
  P.w_uk = (const __nv_bfloat16*)d_in[3];
  P.w_uv = (const __nv_bfloat16*)d_in[4];
  P.w_o = (const __nv_bfloat16*)d_in[5];
  P.w_r = (const __nv_bfloat16*)d_in[7];
  P.w_gate = (const __nv_bfloat16*)d_in[8];
  P.w_up = (const __nv_bfloat16*)d_in[9];
  P.w_down = (const __nv_bfloat16*)d_in[10];
  P.out = (__nv_bfloat16*)d_out;
  cudaLaunchConfig_t cfg = {};
  cfg.gridDim = dim3(NCTA); cfg.blockDim = dim3(384); cfg.dynamicSmemBytes = SMEM_BYTES; cfg.stream = cudaStreamPerThread;
  cudaLaunchAttribute at[1];
  at[0].id = cudaLaunchAttributeClusterDimension; at[0].val.clusterDim.x = 2; at[0].val.clusterDim.y = 1; at[0].val.clusterDim.z = 1;
  cfg.attrs = at; cfg.numAttrs = 1;
  cudaLaunchKernelEx(&cfg, mega_kernel, P);
}
```

```cpp
#include <cuda_runtime.h>
#include <cuda_bf16.h>
#include <cuda.h>
#include <stdint.h>
#include <limits.h>
#include <type_traits>

namespace {

constexpr int DM = 512, NH = 32, FF = 1792;
constexpr int NCTA = 132;
constexpr int NST = 6;
constexpr uint32_t STAGE = 32768;
constexpr uint32_t SM_STG = NST * STAGE;
constexpr uint32_t SM_BAR = SM_STG + 32768;
constexpr uint32_t SMEM_BYTES = SM_BAR + 256 + 1024;
constexpr float QSCALE = 0.08838834764831845f * 1.4426950408889634f;
constexpr uint32_t B_FULL = 0, B_EMPTY = 64, B_STFREE = 128, B_DONE = 144;

struct alignas(64) Params {
  CUtensorMap tm_ckv, tm_wq, tm_wuk, tm_wuv, tm_wo;
  const __nv_bfloat16 *x, *w_q, *w_uk, *w_uv, *w_o, *w_r, *w_gate, *w_up, *w_down;
  __nv_bfloat16* out;
};

struct Flags {
  unsigned long long key[2]; unsigned pad0[28];
  unsigned exit_cnt; unsigned pad1[31];
  unsigned ln_done; unsigned pad2[31];
  unsigned moe_done; unsigned pad3[31];
  unsigned moe_fin; unsigned pad4[31];
  unsigned kv_done[32];
  unsigned q_done[32];
  unsigned ctx[256][8];
};

__device__ Flags g_flags;
__device__ __align__(1024) unsigned char g_kv[(size_t)NH * 2 * 16 * 32768];
__device__ __align__(1024) unsigned char g_xn[(size_t)32 * 8 * 8192];
__device__ __align__(1024) unsigned char g_qc[(size_t)32 * NH * 16384];
__device__ __align__(1024) uint4 g_exch[(size_t)16 * 4 * 3 * 4 * 512];
__device__ float g_ypart[4 * DM];
__device__ __align__(16) uint32_t g_selrow[DM / 2];

__device__ __forceinline__ uint32_t smem_u32(const void* p) { return (uint32_t)__cvta_generic_to_shared(p); }
__device__ __forceinline__ void mbar_init(uint32_t bar, int cnt) {
  asm volatile("mbarrier.init.shared::cta.b64 [%0], %1;" ::"r"(bar), "r"(cnt) : "memory");
}
__device__ __forceinline__ void mbar_expect_tx(uint32_t bar, uint32_t bytes) {
  asm volatile("mbarrier.arrive.expect_tx.shared::cta.b64 _, [%0], %1;" ::"r"(bar), "r"(bytes) : "memory");
}
__device__ __forceinline__ void mbar_arrive(uint32_t bar) {
  asm volatile("mbarrier.arrive.shared::cta.b64 _, [%0];" ::"r"(bar) : "memory");
}
__device__ __forceinline__ uint32_t mapa(uint32_t addr, uint32_t cta) {
  uint32_t r; asm volatile("mapa.shared::cluster.u32 %0, %1, %2;" : "=r"(r) : "r"(addr), "r"(cta)); return r;
}
__device__ __forceinline__ void mbar_arrive_cluster(uint32_t bar, uint32_t cnt) {
  asm volatile("mbarrier.arrive.shared::cluster.b64 _, [%0], %1;" ::"r"(bar), "r"(cnt) : "memory");
}
__device__ __forceinline__ uint32_t mbar_test2(uint32_t b0, uint32_t p0, uint32_t b1, uint32_t p1) {
  uint32_t ok;
  asm volatile("{\n.reg .pred p, q;\nmbarrier.test_wait.parity.shared::cta.b64 p, [%1], %2;\nmbarrier.test_wait.parity.shared::cta.b64 q, [%3], %4;\n"
               "and.pred p, p, q;\nselp.u32 %0, 1, 0, p;\n}\n" : "=r"(ok) : "r"(b0), "r"(p0), "r"(b1), "r"(p1) : "memory");
  return ok;
}
__device__ __forceinline__ bool mbar_try(uint32_t bar, uint32_t parity) {
  uint32_t ok;
  asm volatile("{\n.reg .pred p;\nmbarrier.try_wait.parity.shared::cta.b64 p, [%1], %2;\nselp.u32 %0, 1, 0, p;\n}\n"
               : "=r"(ok) : "r"(bar), "r"(parity) : "memory");
  return ok != 0;
}
__device__ __forceinline__ uint32_t clk32() { uint32_t c; asm volatile("mov.u32 %0, %%clock;" : "=r"(c)); return c; }
constexpr uint32_t TIMEOUT_CLKS = 1u << 30;
__device__ __forceinline__ void mbar_wait(uint32_t bar, uint32_t parity) {
  asm volatile("{\n.reg .pred p;\nWAIT_LOOP:\nmbarrier.try_wait.parity.shared::cta.b64 p, [%0], %1;\n@p bra WAIT_DONE;\nbra WAIT_LOOP;\nWAIT_DONE:\n}\n"
               ::"r"(bar), "r"(parity) : "memory");
}
__device__ __forceinline__ unsigned ld_acquire(const unsigned* p) {
  unsigned v; asm volatile("ld.acquire.gpu.global.u32 %0, [%1];" : "=r"(v) : "l"(p) : "memory"); return v;
}
__device__ __forceinline__ void red_release(unsigned* p, unsigned v) {
  asm volatile("red.release.gpu.global.add.u32 [%0], %1;" ::"l"(p), "r"(v) : "memory");
}
__device__ __forceinline__ void red_relaxed(unsigned* p, unsigned v) {
  asm volatile("red.relaxed.gpu.global.add.u32 [%0], %1;" ::"l"(p), "r"(v) : "memory");
}
__device__ __forceinline__ void st_relaxed128(uint4* p, uint32_t a, uint32_t b, uint32_t c, uint32_t d) {
  asm volatile("{\n.reg .b128 v;\nmov.b128 v, {%1,%2,%3,%4};\nst.relaxed.gpu.global.b128 [%0], v;\n}\n" ::"l"(p), "r"(a), "r"(b), "r"(c), "r"(d) : "memory");
}
__device__ __forceinline__ uint4 ld_relaxed128(const uint4* p) {
  uint4 v;
  asm volatile("{\n.reg .b128 v;\nld.relaxed.gpu.global.b128 v, [%4];\nmov.b128 {%0,%1,%2,%3}, v;\n}\n"
               : "=r"(v.x), "=r"(v.y), "=r"(v.z), "=r"(v.w) : "l"(p) : "memory");
  return v;
}
__device__ __forceinline__ unsigned ld_relaxed(const unsigned* p) {
  unsigned v; asm volatile("ld.relaxed.gpu.global.u32 %0, [%1];" : "=r"(v) : "l"(p) : "memory"); return v;
}
__device__ __forceinline__ bool flag_ok(const unsigned* p, unsigned target) { return (int)(ld_acquire(p) - target) >= 0; }
__device__ __forceinline__ void flag_wait(const unsigned* p, unsigned target) {
  while (!flag_ok(p, target)) { __nanosleep(40); }
}
__device__ __forceinline__ void fence_gpu() { asm volatile("fence.acq_rel.gpu;" ::: "memory"); }
__device__ __forceinline__ void fence_async_global() { asm volatile("fence.proxy.async.global;" ::: "memory"); }
__device__ __forceinline__ void fence_async_smem() { asm volatile("fence.proxy.async.shared::cta;" ::: "memory"); }
__device__ __forceinline__ void bar_sync(int id, int n) { asm volatile("bar.sync %0, %1;" ::"r"(id), "r"(n) : "memory"); }
__device__ __forceinline__ void bar_arrive(int id, int n) { asm volatile("bar.arrive %0, %1;" ::"r"(id), "r"(n) : "memory"); }

__device__ __forceinline__ void bulk_load(uint32_t dst, const void* src, uint32_t bytes, uint32_t bar) {
  asm volatile("cp.async.bulk.shared::cluster.global.mbarrier::complete_tx::bytes [%0], [%1], %2, [%3];"
               ::"r"(dst), "l"(src), "r"(bytes), "r"(bar) : "memory");
}
__device__ __forceinline__ void bulk_load_mc(uint32_t dst, const void* src, uint32_t bytes, uint32_t bar) {
  asm volatile("cp.async.bulk.shared::cluster.global.mbarrier::complete_tx::bytes.multicast::cluster [%0], [%1], %2, [%3], %4;"
               ::"r"(dst), "l"(src), "r"(bytes), "r"(bar), "h"((uint16_t)3) : "memory");
}
__device__ __forceinline__ void tma_load(uint32_t dst, const CUtensorMap* tm, int c0, int c1, uint32_t bar) {
  asm volatile("cp.async.bulk.tensor.2d.shared::cluster.global.mbarrier::complete_tx::bytes [%0], [%1, {%3, %4}], [%2];"
               ::"r"(dst), "l"(tm), "r"(bar), "r"(c0), "r"(c1) : "memory");
}
__device__ __forceinline__ void tma_load_mc(uint32_t dst, const CUtensorMap* tm, int c0, int c1, uint32_t bar) {
  asm volatile("cp.async.bulk.tensor.2d.shared::cluster.global.mbarrier::complete_tx::bytes.multicast::cluster [%0], [%1, {%3, %4}], [%2], %5;"
               ::"r"(dst), "l"(tm), "r"(bar), "r"(c0), "r"(c1), "h"((uint16_t)3) : "memory");
}
__device__ __forceinline__ void bulk_store(void* dst, uint32_t src, uint32_t bytes) {
  asm volatile("cp.async.bulk.global.shared::cta.bulk_group [%0], [%1], %2;" ::"l"(dst), "r"(src), "r"(bytes) : "memory");
}
__device__ __forceinline__ void bulk_commit() { asm volatile("cp.async.bulk.commit_group;" ::: "memory"); }
__device__ __forceinline__ void bulk_wait_read0() { asm volatile("cp.async.bulk.wait_group.read 0;" ::: "memory"); }
__device__ __forceinline__ void bulk_wait0() { asm volatile("cp.async.bulk.wait_group 0;" ::: "memory"); }
__device__ __forceinline__ void l2_prefetch(const void* p, uint32_t bytes) {
  asm volatile("cp.async.bulk.prefetch.L2.global [%0], %1;" ::"l"(p), "r"(bytes) : "memory");
}

#define WG_FENCE() asm volatile("wgmma.fence.sync.aligned;" ::: "memory")
#define WG_COMMIT() asm volatile("wgmma.commit_group.sync.aligned;" ::: "memory")
#define WG_WAIT(n) asm volatile("wgmma.wait_group.sync.aligned %0;" ::"n"(n) : "memory")

#define R8(a, o) "+f"(a[o + 0]), "+f"(a[o + 1]), "+f"(a[o + 2]), "+f"(a[o + 3]), "+f"(a[o + 4]), "+f"(a[o + 5]), "+f"(a[o + 6]), "+f"(a[o + 7])
#define R32(a, o) R8(a, o), R8(a, o + 8), R8(a, o + 16), R8(a, o + 24)
#define R64(a, o) R32(a, o), R32(a, o + 32)
#define ACC64 "{%0,%1,%2,%3,%4,%5,%6,%7,%8,%9,%10,%11,%12,%13,%14,%15,%16,%17,%18,%19,%20,%21,%22,%23,%24,%25,%26,%27,%28,%29,%30,%31," \
              "%32,%33,%34,%35,%36,%37,%38,%39,%40,%41,%42,%43,%44,%45,%46,%47,%48,%49,%50,%51,%52,%53,%54,%55,%56,%57,%58,%59,%60,%61,%62,%63}"

constexpr uint32_t DESC_HI = (1024u >> 4) | (1u << 30);
__device__ __forceinline__ uint32_t desc_lo(uint32_t addr, uint32_t lbo) { return ((addr & 0x3FFFFu) >> 4) | ((lbo >> 4) << 16); }

template <int TB>
__device__ __forceinline__ void mma_rs128(float (&d)[64], uint32_t a0, uint32_t a1, uint32_t a2, uint32_t a3, uint32_t blo, int acc) {
  asm volatile("{\n.reg .pred p;\n.reg .b64 db;\nsetp.ne.b32 p, %69, 0;\nmov.b64 db, {%68, %71};\n"
               "wgmma.mma_async.sync.aligned.m64n128k16.f32.bf16.bf16 " ACC64 ", {%64,%65,%66,%67}, db, p, 1, 1, %70;\n}\n"
               : R64(d, 0) : "r"(a0), "r"(a1), "r"(a2), "r"(a3), "r"(blo), "r"(acc), "n"(TB), "r"(DESC_HI));
}
__device__ __forceinline__ void mma_ss256(float (&d)[128], uint32_t alo, uint32_t blo, int acc) {
  asm volatile("{\n.reg .pred p;\n.reg .b64 da, db;\nsetp.ne.b32 p, %130, 0;\nmov.b64 da, {%128, %131};\nmov.b64 db, {%129, %131};\n"
               "wgmma.mma_async.sync.aligned.m64n256k16.f32.bf16.bf16 "
               "{%0,%1,%2,%3,%4,%5,%6,%7,%8,%9,%10,%11,%12,%13,%14,%15,%16,%17,%18,%19,%20,%21,%22,%23,%24,%25,%26,%27,%28,%29,%30,%31,"
               "%32,%33,%34,%35,%36,%37,%38,%39,%40,%41,%42,%43,%44,%45,%46,%47,%48,%49,%50,%51,%52,%53,%54,%55,%56,%57,%58,%59,%60,%61,%62,%63,"
               "%64,%65,%66,%67,%68,%69,%70,%71,%72,%73,%74,%75,%76,%77,%78,%79,%80,%81,%82,%83,%84,%85,%86,%87,%88,%89,%90,%91,%92,%93,%94,%95,"
               "%96,%97,%98,%99,%100,%101,%102,%103,%104,%105,%106,%107,%108,%109,%110,%111,%112,%113,%114,%115,%116,%117,%118,%119,%120,%121,%122,%123,%124,%125,%126,%127},"
               " da, db, p, 1, 1, 0, 1;\n}\n"
               : R64(d, 0), R64(d, 64) : "r"(alo), "r"(blo), "r"(acc), "r"(DESC_HI));
}
template <int N>
__device__ __forceinline__ void fence_regs(float (&d)[N]) {
#pragma unroll
  for (int i = 0; i < N; i++) asm volatile("" : "+f"(d[i])::"memory");
}
__device__ __forceinline__ uint32_t pack_bf16(float lo, float hi) {
  uint32_t r; asm("cvt.rn.bf16x2.f32 %0, %1, %2;" : "=r"(r) : "f"(hi), "f"(lo)); return r;
}
__device__ __forceinline__ float bf16_round(float v) { return __bfloat162float(__float2bfloat16_rn(v)); }
__device__ __forceinline__ float bf_lo(uint32_t v) { return __uint_as_float(v << 16); }
__device__ __forceinline__ float bf_hi(uint32_t v) { return __uint_as_float(v & 0xFFFF0000u); }
__device__ __forceinline__ float ex2(float x) { float y; asm("ex2.approx.ftz.f32 %0, %1;" : "=f"(y) : "f"(x)); return y; }
__device__ __forceinline__ void stmatrix4(uint32_t addr, uint32_t r0, uint32_t r1, uint32_t r2, uint32_t r3) {
  asm volatile("stmatrix.sync.aligned.m8n8.x4.shared.b16 [%0], {%1,%2,%3,%4};" ::"r"(addr), "r"(r0), "r"(r1), "r"(r2), "r"(r3) : "memory");
}
__device__ __forceinline__ void ldmatrix4(uint32_t addr, uint32_t& r0, uint32_t& r1, uint32_t& r2, uint32_t& r3) {
  asm volatile("ldmatrix.sync.aligned.m8n8.x4.shared.b16 {%0,%1,%2,%3}, [%4];" : "=r"(r0), "=r"(r1), "=r"(r2), "=r"(r3) : "r"(addr) : "memory");
}
__device__ __forceinline__ void mma_16816(float* c, const uint32_t* a, uint32_t b0, uint32_t b1) {
  asm volatile("mma.sync.aligned.m16n8k16.row.col.f32.bf16.bf16.f32 {%0,%1,%2,%3}, {%4,%5,%6,%7}, {%8,%9}, {%0,%1,%2,%3};"
               : "+f"(c[0]), "+f"(c[1]), "+f"(c[2]), "+f"(c[3]) : "r"(a[0]), "r"(a[1]), "r"(a[2]), "r"(a[3]), "r"(b0), "r"(b1));
}
__device__ __forceinline__ void cluster_arrive() { asm volatile("barrier.cluster.arrive.relaxed;" ::: "memory"); }
__device__ __forceinline__ void cluster_wait() { asm volatile("barrier.cluster.wait;" ::: "memory"); }

__device__ __forceinline__ uint32_t read_epoch() {
  uint32_t v; asm volatile("ld.relaxed.gpu.global.u32 %0, [%1];" : "=r"(v) : "l"(&g_flags.exit_cnt) : "memory");
  return v / NCTA;
}
__device__ __forceinline__ uint32_t rnext(uint32_t r) { r += 8; return r >= NST * 8 ? (r - NST * 8) ^ 1u : r; }

#define PROF(role, slot) do { } while (0)
#define PROFC(slot) do { } while (0)

struct Cons {
  uint32_t sb;
  uint32_t bars;
  int w;
  int warp;
  int lane;
  uint32_t rank;
  uint32_t ring;
  uint32_t stphase;
  uint32_t epoch;
  uint32_t ebase;
  __device__ __forceinline__ void wait_full(uint32_t r) { mbar_wait(bars + B_FULL + (r & ~7u), r & 1u); }
  __device__ __forceinline__ uint32_t stage_addr(uint32_t r) { return sb + ((r & ~7u) << 12); }
  __device__ __forceinline__ void release(uint32_t r, uint32_t n = 1) { if (ebase) mbar_arrive_cluster(ebase + (r & ~7u), n); }
  __device__ __forceinline__ void turn_sync() { bar_sync(1 + w, 256); }
  __device__ __forceinline__ void turn_pass() { bar_arrive(2 - w, 256); }
  __device__ __forceinline__ uint32_t frag_off() {
    const int mat = lane >> 3;
    return (warp * 16 + (mat & 1) * 8 + (lane & 7)) * 128 + ((((mat >> 1) ^ lane) & 7) << 4);
  }
  __device__ __forceinline__ void stage_out(const float (&a)[64], float s0, float s1) {
    mbar_wait(bars + B_STFREE + w * 8, stphase); stphase ^= 1;
    const uint32_t base = sb + SM_STG + w * 16384 + frag_off();
#pragma unroll
    for (int jj = 0; jj < 8; jj++) {
      const uint32_t r0 = pack_bf16(a[8 * jj + 0] * s0, a[8 * jj + 1] * s0), r1 = pack_bf16(a[8 * jj + 2] * s1, a[8 * jj + 3] * s1);
      const uint32_t r2 = pack_bf16(a[8 * jj + 4] * s0, a[8 * jj + 5] * s0), r3 = pack_bf16(a[8 * jj + 6] * s1, a[8 * jj + 7] * s1);
      stmatrix4((base ^ (((2 * jj) & 7) << 4)) + (jj >> 2) * 8192, r0, r1, r2, r3);
    }
    fence_async_smem();
    bar_arrive(3 + w, 160);
  }
};

__device__ __forceinline__ void ln_row(const Params& P, int row, int lane, uint32_t epoch) {
  uint4 v[2], wr[2];
  const uint4* xr = reinterpret_cast<const uint4*>(P.x + (size_t)row * DM);
  v[0] = __ldg(xr + lane); v[1] = __ldg(xr + lane + 32);
  wr[0] = __ldg(reinterpret_cast<const uint4*>(P.w_r) + lane); wr[1] = __ldg(reinterpret_cast<const uint4*>(P.w_r) + lane + 32);
  float f[16];
#pragma unroll
  for (int c = 0; c < 2; c++) {
    const uint32_t u[4] = {v[c].x, v[c].y, v[c].z, v[c].w};
#pragma unroll
    for (int e = 0; e < 4; e++) { f[c * 8 + 2 * e] = bf_lo(u[e]); f[c * 8 + 2 * e + 1] = bf_hi(u[e]); }
  }
  float s = 0.f;
#pragma unroll
  for (int e = 0; e < 16; e++) s += f[e];
#pragma unroll
  for (int o = 16; o > 0; o >>= 1) s += __shfl_xor_sync(0xffffffffu, s, o);
  const float mean = s * (1.0f / DM);
  float q = 0.f;
#pragma unroll
  for (int e = 0; e < 16; e++) { float d = f[e] - mean; q += d * d; }
#pragma unroll
  for (int o = 16; o > 0; o >>= 1) q += __shfl_xor_sync(0xffffffffu, q, o);
  const float m = bf16_round(mean);
  const float var = bf16_round(q * (1.0f / DM));
  const float rs = 1.0f / bf16_round(sqrtf(bf16_round(var + 1e-5f)));
  float r = 0.f;
  const int g = row >> 6, rl = row & 63;
#pragma unroll
  for (int c = 0; c < 2; c++) {
    const uint32_t wu[4] = {wr[c].x, wr[c].y, wr[c].z, wr[c].w};
    uint32_t o[4];
#pragma unroll
    for (int e = 0; e < 4; e++) {
      const uint32_t d = pack_bf16(f[c * 8 + 2 * e] - m, f[c * 8 + 2 * e + 1] - m);
      o[e] = pack_bf16(bf_lo(d) * rs, bf_hi(d) * rs);
      r += bf_lo(o[e]) * bf_lo(wu[e]); r += bf_hi(o[e]) * bf_hi(wu[e]);
    }
    const int c8 = lane + 32 * c, kh = c8 >> 3, ch = c8 & 7;
    *reinterpret_cast<uint4*>(g_xn + ((size_t)(g * 8 + kh) * 64 + rl) * 128 + ((ch ^ (rl & 7)) << 4)) = make_uint4(o[0], o[1], o[2], o[3]);
  }
#pragma unroll
  for (int o = 16; o > 0; o >>= 1) r += __shfl_xor_sync(0xffffffffu, r, o);
  uint32_t u = __float_as_uint(bf16_round(r) + 0.0f);
  u = (u & 0x80000000u) ? ~u : (u | 0x80000000u);
  const unsigned long long key = ((unsigned long long)u << 32) | (unsigned long long)(0xFFFFFFFFu - (uint32_t)row);
  if (lane == 0) asm volatile("red.relaxed.gpu.global.max.u64 [%0], %1;" ::"l"(&g_flags.key[epoch & 1]), "l"(key) : "memory");
}

__device__ __forceinline__ void proj_phase(Cons& C, const Params& P) {
  uint32_t af[128];
  float acc[64];
#pragma unroll 1
  for (int ph = 0; ph < 2; ph++) {
    {
      uint32_t r = C.ring;
      if (C.w == 0) { C.wait_full(r); C.wait_full(rnext(r)); bar_arrive(8, 256); }
      else { bar_sync(8, 256); r ^= 1u; }
      const uint32_t off = C.frag_off();
#pragma unroll
      for (int st = 0; st < 2; st++) {
        C.wait_full(r);
        const uint32_t base = C.stage_addr(r) + off;
#pragma unroll
        for (int kk = 0; kk < 16; kk++)
          ldmatrix4((base ^ ((2 * (kk & 3)) << 4)) + (kk >> 2) * 8192, af[st * 64 + kk * 4], af[st * 64 + kk * 4 + 1], af[st * 64 + kk * 4 + 2],
                    af[st * 64 + kk * 4 + 3]);
        __syncwarp();
        C.release(r, 2);
        r = rnext(r);
      }
      C.ring = rnext(rnext(C.ring));
    }
    const int nt = ph ? 4 : 8;
#pragma unroll 1
    for (int t = 0; t < nt; t++) {
      uint32_t prev = 0;
      C.turn_sync();
#pragma unroll
      for (int c = 0; c < 4; c++) {
        C.wait_full(C.ring);
        const uint32_t blo = desc_lo(C.stage_addr(C.ring), 16384);
        WG_FENCE();
#pragma unroll
        for (int kk = 0; kk < 8; kk++)
          mma_rs128<1>(acc, af[c * 32 + kk * 4], af[c * 32 + kk * 4 + 1], af[c * 32 + kk * 4 + 2], af[c * 32 + kk * 4 + 3], blo + kk * 128,
                       (c | kk) != 0);
        WG_COMMIT();
        if (c == 3) C.turn_pass();
        if (c > 0) { WG_WAIT(1); C.release(prev); }
        prev = C.ring;
        C.ring = rnext(C.ring);
      }
      if (t == 0) C.ring = rnext(rnext(C.ring));
      WG_WAIT(0);
      C.release(prev);
      fence_regs(acc);
      const float sc = ph ? QSCALE : 1.0f;
      C.stage_out(acc, sc, sc);
      PROFC(ph * 8 + t);
      if (ph == 0) {
        if (t == 0) C.epoch = read_epoch();
        if (t == 1 || t == 2) ln_row(P, blockIdx.x * 16 + (C.w * 4 + C.warp) * 2 + t - 1, C.lane, C.epoch);
      }
    }
  }
}

__device__ __forceinline__ void att_phase(Cons& C, const int a) {
  constexpr int P1 = 9;
  float s[64], o[64];
  uint32_t q[32], p[32];
#pragma unroll
  for (int i = 0; i < 64; i++) o[i] = 0.f;
#pragma unroll
  for (int i = 0; i < 32; i++) p[i] = 0u;
  const uint32_t qoff = C.w * 16384 + C.frag_off();
  auto load_q = [&](uint32_t r) {
    C.wait_full(r);
    const uint32_t base = C.stage_addr(r) + qoff;
#pragma unroll
    for (int kk = 0; kk < 8; kk++) ldmatrix4((base ^ ((2 * (kk & 3)) << 4)) + (kk >> 2) * 8192, q[4 * kk], q[4 * kk + 1], q[4 * kk + 2], q[4 * kk + 3]);
    __syncwarp();
    C.release(r);
  };
  uint32_t ring = C.ring, qr = ring, kr, vr = 0;
  load_q(qr);
  ring = rnext(ring);
  kr = ring; ring = rnext(ring);
  C.wait_full(kr);
  const int sw = a + 1 - C.w;
  float m0 = 0.f, m1 = 0.f, l0 = 1.f, l1 = 1.f, a0 = 1.f, a1 = 1.f;
  bool usem = false;
  int st = 0, gs = 0, pvacc = 0;
  auto step = [&](auto fast_tag) {
    constexpr bool FAST = decltype(fast_tag)::value;
    const uint32_t klo = desc_lo(C.stage_addr(kr), 16), vlo = desc_lo(C.stage_addr(vr), 16384);
    C.turn_sync();
    WG_FENCE();
#pragma unroll
    for (int kk = 0; kk < 8; kk++)
      mma_rs128<0>(s, q[4 * kk], q[4 * kk + 1], q[4 * kk + 2], q[4 * kk + 3], klo + (((kk >> 2) * 16384 + (kk & 3) * 32) >> 4), kk != 0);
    WG_COMMIT();
    if (FAST || gs > 0) {
      if (!FAST) WG_FENCE();
#pragma unroll
      for (int kk = 0; kk < 8; kk++) mma_rs128<1>(o, p[4 * kk], p[4 * kk + 1], p[4 * kk + 2], p[4 * kk + 3], vlo + kk * 128, kk ? 1 : pvacc);
      WG_COMMIT();
    } else {
      WG_COMMIT();
    }
    C.turn_pass();
    const uint32_t ck = kr, cv = vr;
    const bool first = !FAST && (st == 0 || st == sw), last = !FAST && gs == 33;
    const int ns = (!FAST && st == 16) ? 0 : st + 1;
    if (FAST) {
      kr = ring; vr = rnext(kr); ring = rnext(vr);
    } else {
      if (ns == a || (ns == 0 && !last)) { qr = ring; ring = rnext(ring); }
      if (!last) {
        kr = ring; ring = rnext(ring);
        if (ns == a) { if (C.w) kr = ring; ring = rnext(ring); }
      }
      vr = ring; ring = rnext(ring);
      if (ns == a + 1) { if (C.w) vr = ring; ring = rnext(ring); }
      if (last) kr = vr;
      if (first) {
        l0 += __shfl_xor_sync(0xffffffffu, l0, 1); l1 += __shfl_xor_sync(0xffffffffu, l1, 1);
        l0 += __shfl_xor_sync(0xffffffffu, l0, 2); l1 += __shfl_xor_sync(0xffffffffu, l1, 2);
        a0 = __fdividef(1.0f, l0); a1 = __fdividef(1.0f, l1);
        l0 = 0.f; l1 = 0.f; m0 = 0.f; m1 = 0.f; usem = false;
      }
    }
    const bool diag = !FAST && (st == sw - 1 || st == sw);
    auto mask = [&]() {
      const int odd = (int)C.rank ^ C.w ^ (st == sw ? 0 : 1);
      const int lim0 = odd * 64 + C.warp * 16 + (C.lane >> 2) - 2 * (C.lane & 3);
      const int lim1 = lim0 + 8;
#pragma unroll
      for (int i = 0; i < 16; i++) {
        if (8 * i > lim0) s[4 * i] = -INFINITY;
        if (8 * i + 1 > lim0) s[4 * i + 1] = -INFINITY;
        if (8 * i > lim1) s[4 * i + 2] = -INFINITY;
        if (8 * i + 1 > lim1) s[4 * i + 3] = -INFINITY;
      }
    };
    WG_WAIT(1);
    fence_regs(s);
    if (diag) mask();
    if (__builtin_expect(usem, 0)) {
#pragma unroll
      for (int i = 0; i < 16; i++) { s[4 * i] -= m0; s[4 * i + 1] -= m0; s[4 * i + 2] -= m1; s[4 * i + 3] -= m1; }
    }
    const uint32_t ready = mbar_test2(C.bars + B_FULL + (kr & ~7u), kr & 1u, C.bars + B_FULL + (vr & ~7u), vr & 1u);
    float t0 = 0.f, t1 = 0.f;
#pragma unroll
    for (int i = 0; i < P1; i++) {
      s[4 * i] = ex2(s[4 * i]); s[4 * i + 1] = ex2(s[4 * i + 1]); s[4 * i + 2] = ex2(s[4 * i + 2]); s[4 * i + 3] = ex2(s[4 * i + 3]);
      if (i == 0) { t0 = s[0] + s[1]; t1 = s[2] + s[3]; }
      else { t0 += s[4 * i] + s[4 * i + 1]; t1 += s[4 * i + 2] + s[4 * i + 3]; }
    }
    if (__builtin_expect(!ready || !(t0 + t1 <= 0x1p30f), 0)) { C.wait_full(kr); C.wait_full(vr); }
    WG_WAIT(0);
    fence_regs(o);
    if (FAST || gs > 0) {
      C.release(cv, (!FAST && st == a + 1) ? 2 : 1);
      if (first) C.stage_out(o, a0, a1);
    }
#pragma unroll
    for (int i = 0; i < 16; i++) {
      if (i >= P1) {
        s[4 * i] = ex2(s[4 * i]); s[4 * i + 1] = ex2(s[4 * i + 1]); s[4 * i + 2] = ex2(s[4 * i + 2]); s[4 * i + 3] = ex2(s[4 * i + 3]);
        t0 += s[4 * i] + s[4 * i + 1]; t1 += s[4 * i + 2] + s[4 * i + 3];
      }
      p[2 * i] = pack_bf16(s[4 * i], s[4 * i + 1]); p[2 * i + 1] = pack_bf16(s[4 * i + 2], s[4 * i + 3]);
    }
    bool bad = !(t0 <= 0x1p30f && t1 <= 0x1p30f);
    if (first) {
      float u0 = t0 + __shfl_xor_sync(0xffffffffu, t0, 1), u1 = t1 + __shfl_xor_sync(0xffffffffu, t1, 1);
      u0 += __shfl_xor_sync(0xffffffffu, u0, 2); u1 += __shfl_xor_sync(0xffffffffu, u1, 2);
      bad = bad || !(u0 >= 0x1p-30f && u1 >= 0x1p-30f);
    }
    if (__builtin_expect(__any_sync(0xffffffffu, bad), 0)) {
      const uint32_t kbase = C.stage_addr(ck) + ((C.lane >> 4) * 8 + (C.lane & 7)) * 128 + (((((C.lane >> 3) & 1) ^ C.lane) & 7) << 4);
#pragma unroll
      for (int i = 0; i < 64; i++) s[i] = 0.f;
#pragma unroll
      for (int kk = 0; kk < 8; kk++) {
#pragma unroll
        for (int jp = 0; jp < 8; jp++) {
          uint32_t b0, b1, b2, b3;
          ldmatrix4((kbase ^ ((2 * (kk & 3)) << 4)) + (kk >> 2) * 16384 + jp * 2048, b0, b1, b2, b3);
          mma_16816(s + 8 * jp, q + 4 * kk, b0, b1);
          mma_16816(s + 8 * jp + 4, q + 4 * kk, b2, b3);
        }
      }
      if (diag) mask();
      float n0 = fmaxf(s[0], s[1]), n1 = fmaxf(s[2], s[3]);
#pragma unroll
      for (int i = 1; i < 16; i++) { n0 = fmaxf(n0, fmaxf(s[4 * i], s[4 * i + 1])); n1 = fmaxf(n1, fmaxf(s[4 * i + 2], s[4 * i + 3])); }
      n0 = fmaxf(n0, __shfl_xor_sync(0xffffffffu, n0, 1)); n1 = fmaxf(n1, __shfl_xor_sync(0xffffffffu, n1, 1));
      n0 = fmaxf(n0, __shfl_xor_sync(0xffffffffu, n0, 2)); n1 = fmaxf(n1, __shfl_xor_sync(0xffffffffu, n1, 2));
      if (!first) {
        n0 = fmaxf(n0, m0); n1 = fmaxf(n1, m1);
        const float f0 = ex2(m0 - n0), f1 = ex2(m1 - n1);
        l0 *= f0; l1 *= f1;
#pragma unroll
        for (int i = 0; i < 16; i++) { o[4 * i] *= f0; o[4 * i + 1] *= f0; o[4 * i + 2] *= f1; o[4 * i + 3] *= f1; }
      }
      m0 = n0; m1 = n1; usem = true;
      t0 = 0.f; t1 = 0.f;
#pragma unroll
      for (int i = 0; i < 16; i++) {
        const float e0 = ex2(s[4 * i] - m0), e1 = ex2(s[4 * i + 1] - m0), e2 = ex2(s[4 * i + 2] - m1), e3 = ex2(s[4 * i + 3] - m1);
        t0 += e0 + e1; t1 += e2 + e3;
        p[2 * i] = pack_bf16(e0, e1); p[2 * i + 1] = pack_bf16(e2, e3);
      }
      __syncwarp();
    }
    l0 += t0; l1 += t1;
    C.release(ck, (!FAST && st == a) ? 2 : 1);
    if (!FAST && (ns == sw || (ns == 0 && !last))) load_q(qr);
    pvacc = first ? 0 : 1;
    st = ns;
    PROFC(13 + gs);
    gs++;
  };
  const uint32_t special = 1u | (7u << (a - 1)) | (1u << 16);
  PROFC(12);
#pragma unroll 1
  while (gs < 34) {
    step(std::false_type());
#pragma unroll 1
    while (!((special >> st) & 1u)) step(std::true_type());
  }
  {
    const uint32_t vlo = desc_lo(C.stage_addr(vr), 16384);
    C.turn_sync();
    WG_FENCE();
#pragma unroll
    for (int kk = 0; kk < 8; kk++) mma_rs128<1>(o, p[4 * kk], p[4 * kk + 1], p[4 * kk + 2], p[4 * kk + 3], vlo + kk * 128, kk ? 1 : pvacc);
    WG_COMMIT();
    if (C.w == 0) C.turn_pass();
    l0 += __shfl_xor_sync(0xffffffffu, l0, 1); l1 += __shfl_xor_sync(0xffffffffu, l1, 1);
    l0 += __shfl_xor_sync(0xffffffffu, l0, 2); l1 += __shfl_xor_sync(0xffffffffu, l1, 2);
    a0 = __fdividef(1.0f, l0); a1 = __fdividef(1.0f, l1);
    WG_WAIT(0);
    C.release(vr);
    fence_regs(o);
    C.stage_out(o, a0, a1);
    PROFC(47);
  }
  C.ring = ring;
}

__device__ __forceinline__ void op_phase(Cons& C, const Params& P, int j, int nh, int ks) {
  float acc[128];
#pragma unroll
  for (int i = 0; i < 128; i++) acc[i] = 0.f;
  uint32_t pa = 0, pb = 0;
  const int sel = (int)(0xFFFFFFFFu - (uint32_t)__ldcg(&g_flags.key[C.epoch & 1]));
  const int tid = C.warp * 32 + C.lane;
  const int g = 4 * j + 2 * (int)C.rank + C.w;
  const int kh = 4 * nh + ks;
  if ((sel >> 4) == g * 4 + C.warp) { flag_wait(&g_flags.moe_fin, C.epoch + 1); __syncwarp(); }
  uint4 xv[4], nv[4];
#pragma unroll
  for (int i = 0; i < 4; i++) {
    const int idx = C.warp * 128 + C.lane + 32 * i, row = idx >> 3, ch = (idx ^ row) & 7;
    xv[i] = __ldg(reinterpret_cast<const uint4*>(P.x + (size_t)(g * 64 + row) * DM + kh * 64 + ch * 8));
    const uint4* np = reinterpret_cast<const uint4*>(g_xn + (size_t)(g * 8 + kh) * 8192) + idx;
    if (g * 64 + row == sel) np = reinterpret_cast<const uint4*>(g_selrow) + kh * 8 + ch;
    nv[i] = __ldcg(np);
  }
#pragma unroll 1
  for (int t = 0; t < 8; t++) {
    const uint32_t ia = C.ring, i0 = rnext(ia), i1 = rnext(i0);
    C.ring = rnext(i1);
    C.wait_full(ia);
    const uint32_t alo = desc_lo(C.stage_addr(ia) + C.w * 16384, 16);
    C.wait_full(i0);
    const uint32_t b0 = desc_lo(C.stage_addr(i0), 8192);
    WG_FENCE();
#pragma unroll
    for (int kk = 0; kk < 4; kk++) mma_ss256(acc, alo + kk * 2, b0 + kk * 128, 1);
    WG_COMMIT();
    if (t > 0) { WG_WAIT(1); if (t < 7) { C.release(pa); C.release(pb); } }
    C.wait_full(i1);
    const uint32_t b1 = desc_lo(C.stage_addr(i1), 8192);
    WG_FENCE();
#pragma unroll
    for (int kk = 0; kk < 4; kk++) mma_ss256(acc, alo + 512 + kk * 2, b1 + kk * 128, 1);
    WG_COMMIT();
    WG_WAIT(1);
    if (t < 6) C.release(i0);
    pa = ia; pb = i1;
  }
  cluster_arrive();
  WG_WAIT(0);
  fence_regs(acc);
  PROFC(48);
  const int tile = j * 2 + nh, sub = (int)C.rank * 2 + C.w;
  const uint32_t tag = ~C.epoch & 1u;
#pragma unroll
  for (int pp = 1; pp < 4; pp++) {
    uint4* dst = g_exch + (size_t)(((tile * 4 + ((pp + ks) & 3)) * 3 + (pp - 1)) * 4 + sub) * 512 + tid;
#pragma unroll
    for (int v = 0; v < 4; v++) {
      const float* f = acc + 32 * pp + 8 * v;
      st_relaxed128(dst + v * 128, (pack_bf16(f[0], f[1]) & ~1u) | tag, pack_bf16(f[2], f[3]), pack_bf16(f[4], f[5]), pack_bf16(f[6], f[7]));
    }
  }
  __syncwarp();
  if (C.lane < 3) red_relaxed(&g_flags.ctx[(tile * 4 + ((C.lane + 1 + ks) & 3)) * 4 + sub][4 + C.warp], 1);
  PROFC(49);
  if (C.lane == 0) {
    const unsigned* hint = &g_flags.ctx[(tile * 4 + ks) * 4 + sub][4 + C.warp];
    while ((int)(ld_relaxed(hint) - (C.epoch + 1) * 3) < 0) {}
  }
  __syncwarp();
  PROFC(50);
  const uint4* src = g_exch + (size_t)((tile * 4 + ks) * 3 * 4 + sub) * 512 + tid;
  uint4 e[12];
#pragma unroll 1
  for (;;) {
    uint32_t any = 0, all = 1;
#pragma unroll
    for (int i = 0; i < 12; i++) e[i] = ld_relaxed128(src + (i >> 2) * 2048 + (i & 3) * 128);
#pragma unroll
    for (int i = 0; i < 12; i++) { any |= e[i].x; all &= e[i].x; }
    if (__all_sync(0xffffffffu, ((tag ? all : ~any) & 1u) != 0u)) break;
  }
  PROFC(52);
#pragma unroll
  for (int i = 0; i < 12; i++) {
    float* d = acc + 8 * (i & 3);
    d[0] += bf_lo(e[i].x); d[1] += bf_hi(e[i].x); d[2] += bf_lo(e[i].y); d[3] += bf_hi(e[i].y);
    d[4] += bf_lo(e[i].z); d[5] += bf_hi(e[i].z); d[6] += bf_lo(e[i].w); d[7] += bf_hi(e[i].w);
  }
  mbar_wait(C.bars + B_STFREE + C.w * 8, C.stphase);
  const uint32_t stg = C.sb + SM_STG + C.w * 16384;
  {
    const uint32_t base = stg + C.frag_off();
#pragma unroll
    for (int jj = 0; jj < 4; jj++)
      stmatrix4(base ^ ((2 * jj) << 4), pack_bf16(acc[8 * jj], acc[8 * jj + 1]), pack_bf16(acc[8 * jj + 2], acc[8 * jj + 3]),
                pack_bf16(acc[8 * jj + 4], acc[8 * jj + 5]), pack_bf16(acc[8 * jj + 6], acc[8 * jj + 7]));
  }
  __syncwarp();
  PROFC(54);
#pragma unroll
  for (int i = 0; i < 4; i++) {
    const int idx = C.warp * 128 + C.lane + 32 * i, row = idx >> 3, ch = (idx ^ row) & 7;
    uint4 av;
    asm volatile("ld.shared.v4.u32 {%0,%1,%2,%3}, [%4];" : "=r"(av.x), "=r"(av.y), "=r"(av.z), "=r"(av.w) : "r"(stg + idx * 16) : "memory");
    const uint32_t au[4] = {av.x, av.y, av.z, av.w}, xu[4] = {xv[i].x, xv[i].y, xv[i].z, xv[i].w}, nu[4] = {nv[i].x, nv[i].y, nv[i].z, nv[i].w};
    uint32_t ou[4];
#pragma unroll
    for (int e2 = 0; e2 < 4; e2++) {
      const uint32_t xa = pack_bf16(bf_lo(xu[e2]) + bf_lo(au[e2]), bf_hi(xu[e2]) + bf_hi(au[e2]));
      ou[e2] = pack_bf16(bf_lo(xa) + bf_lo(nu[e2]), bf_hi(xa) + bf_hi(nu[e2]));
    }
    *reinterpret_cast<uint4*>(P.out + (size_t)(g * 64 + row) * DM + kh * 64 + ch * 8) = make_uint4(ou[0], ou[1], ou[2], ou[3]);
  }
  PROFC(51);
}

__device__ __forceinline__ void moe_phase(Cons& C, const Params& P, int part, unsigned char* smem) {
  const int tid = C.w * 128 + C.warp * 32 + C.lane;
  float* xs = reinterpret_cast<float*>(smem + SM_STG);
  float* hs = xs + 512;
  float* red = xs + 1024;
  if (tid == 0) flag_wait(&g_flags.ln_done, (C.epoch + 1) * 256);
  bar_sync(5, 256);
  const unsigned long long key = __ldcg(&g_flags.key[C.epoch & 1]);
  const int sel = (int)(0xFFFFFFFFu - (uint32_t)key);
  {
    const int g = sel >> 6, rl = sel & 63;
    const int c2 = tid * 2, kh = c2 >> 6, ch = (c2 >> 3) & 7;
    const uint32_t u = __ldcg(reinterpret_cast<const uint32_t*>(g_xn + ((size_t)(g * 8 + kh) * 64 + rl) * 128 + ((ch ^ (rl & 7)) << 4) + (c2 & 7) * 2));
    xs[c2] = bf_lo(u); xs[c2 + 1] = bf_hi(u);
  }
  bar_sync(5, 256);
  if (tid < 224) {
    const int chunk = tid % 56, kg = tid / 56;
    const uint4* wg = reinterpret_cast<const uint4*>(P.w_gate + (size_t)kg * 128 * FF + part * 448 + chunk * 8);
    const uint4* wu = reinterpret_cast<const uint4*>(P.w_up + (size_t)kg * 128 * FF + part * 448 + chunk * 8);
    float ag[8], au[8];
#pragma unroll
    for (int e = 0; e < 8; e++) { ag[e] = 0.f; au[e] = 0.f; }
#pragma unroll 1
    for (int k0 = 0; k0 < 128; k0 += 16) {
      uint4 vg[16], vu[16];
#pragma unroll
      for (int i = 0; i < 16; i++) { vg[i] = __ldg(wg + (size_t)(k0 + i) * (FF / 8)); vu[i] = __ldg(wu + (size_t)(k0 + i) * (FF / 8)); }
#pragma unroll
      for (int i = 0; i < 16; i++) {
        const float xk = xs[kg * 128 + k0 + i];
        const uint32_t a[4] = {vg[i].x, vg[i].y, vg[i].z, vg[i].w}, b[4] = {vu[i].x, vu[i].y, vu[i].z, vu[i].w};
#pragma unroll
        for (int e = 0; e < 4; e++) {
          ag[2 * e] += xk * bf_lo(a[e]); ag[2 * e + 1] += xk * bf_hi(a[e]);
          au[2 * e] += xk * bf_lo(b[e]); au[2 * e + 1] += xk * bf_hi(b[e]);
        }
      }
    }
#pragma unroll
    for (int e = 0; e < 8; e++) { red[(kg * 2) * 448 + chunk * 8 + e] = ag[e]; red[(kg * 2 + 1) * 448 + chunk * 8 + e] = au[e]; }
  }
  bar_sync(5, 256);
  for (int f = tid; f < 448; f += 256) {
    float gs = 0.f, us = 0.f;
#pragma unroll
    for (int kg = 0; kg < 4; kg++) { gs += red[(kg * 2) * 448 + f]; us += red[(kg * 2 + 1) * 448 + f]; }
    gs = bf16_round(gs); us = bf16_round(us);
    const float sl = bf16_round(gs / (1.0f + expf(-gs)));
    hs[f] = bf16_round(sl * us);
  }
  bar_sync(5, 256);
  {
    const int chunk = tid & 63, rg = tid >> 6;
    const uint4* wd = reinterpret_cast<const uint4*>(P.w_down + (size_t)(part * 448 + rg * 112) * DM + chunk * 8);
    float ay[8];
#pragma unroll
    for (int e = 0; e < 8; e++) ay[e] = 0.f;
#pragma unroll 1
    for (int k0 = 0; k0 < 112; k0 += 28) {
      uint4 v[28];
#pragma unroll
      for (int i = 0; i < 28; i++) v[i] = __ldg(wd + (size_t)(k0 + i) * (DM / 8));
#pragma unroll
      for (int i = 0; i < 28; i++) {
        const float hk = hs[rg * 112 + k0 + i];
        const uint32_t a[4] = {v[i].x, v[i].y, v[i].z, v[i].w};
#pragma unroll
        for (int e = 0; e < 4; e++) { ay[2 * e] += hk * bf_lo(a[e]); ay[2 * e + 1] += hk * bf_hi(a[e]); }
      }
    }
#pragma unroll
    for (int e = 0; e < 8; e++) red[rg * 512 + chunk * 8 + e] = ay[e];
  }
  bar_sync(5, 256);
  for (int c = tid; c < DM; c += 256) g_ypart[part * DM + c] = red[c] + red[512 + c] + red[1024 + c] + red[1536 + c];
  bar_sync(5, 256);
  if (tid == 0) red_release(&g_flags.moe_done, 1);
  if (part == 0) {
    if (tid == 0) flag_wait(&g_flags.moe_done, (C.epoch + 1) * 4);
    bar_sync(5, 256);
    uint32_t ub = (uint32_t)(key >> 32);
    ub = (ub & 0x80000000u) ? (ub & 0x7FFFFFFFu) : ~ub;
    const float sig = bf16_round(1.0f / (1.0f + expf(-__uint_as_float(ub))));
    float y0 = 0.f, y1 = 0.f;
#pragma unroll
    for (int c = 0; c < 4; c++) { y0 += __ldcg(&g_ypart[c * DM + 2 * tid]); y1 += __ldcg(&g_ypart[c * DM + 2 * tid + 1]); }
    y0 = bf16_round(bf16_round(y0) * sig); y1 = bf16_round(bf16_round(y1) * sig);
    g_selrow[tid] = pack_bf16(xs[2 * tid] + y0, xs[2 * tid + 1] + y1);
    bar_sync(5, 256);
    if (tid == 0) red_release(&g_flags.moe_fin, 1);
  }
}

__device__ __forceinline__ int proj_head(int t, int cg) {
  if (t < 8) return (t < 4 ? 16 : 0) + 2 * cg + ((t >> 1) & 1);
  return (t < 10 ? 0 : 16) + 2 * cg + (t & 1);
}

__global__ void __launch_bounds__(384, 1) mega_kernel(const __grid_constant__ Params P) {
  extern __shared__ unsigned char smem_raw[];
  const uint32_t sraw = smem_u32(smem_raw);
  const uint32_t sb = (sraw + 1023u) & ~1023u;
  const uint32_t bars = sb + SM_BAR;
  const int warp_id = __shfl_sync(0xffffffffu, threadIdx.x >> 5, 0);
  const int lane = threadIdx.x & 31;
  uint32_t rank; asm volatile("mov.u32 %0, %%cluster_ctarank;" : "=r"(rank));
  const int pair = blockIdx.x >> 1;
  const bool spare = pair >= 64;
  const int jx = (pair & 3) + (pair & 4);
  const int a = 2 * jx + 1;

  if (threadIdx.x == 0) {
    for (int s = 0; s < NST; s++) { mbar_init(bars + B_FULL + s * 8, 1); mbar_init(bars + B_EMPTY + s * 8, 16); }
    mbar_init(bars + B_STFREE, 1); mbar_init(bars + B_STFREE + 8, 1);
    mbar_init(bars + B_DONE, 11);
    asm volatile("fence.mbarrier_init.release.cluster;" ::: "memory");
  }
  __syncthreads();
  asm volatile("barrier.cluster.arrive.relaxed.aligned;\nbarrier.cluster.wait.aligned;" ::: "memory");

  if (warp_id < 4) {
    asm volatile("setmaxnreg.dec.sync.aligned.u32 40;");
    if (warp_id == 0) {
      if (spare) {
        __nanosleep(4000);
        const int part = (pair - 64) * 2 + (int)rank;
        for (int i = lane; i < 512; i += 32) {
          l2_prefetch(P.w_gate + (size_t)i * FF + part * 448, 896);
          l2_prefetch(P.w_up + (size_t)i * FF + part * 448, 896);
        }
        if (lane < 28) l2_prefetch(P.w_down + (size_t)(part * 448 + lane * 16) * DM, 16384);
        if (blockIdx.x == 128 && lane == 0) g_flags.key[(read_epoch() + 1) & 1] = 0;
      } else {
        uint32_t ring = 1, fb = 0, epoch = 0;
        auto acquire = [&]() -> uint32_t {
          mbar_wait(bars + B_EMPTY + (ring & ~7u), ring & 1u);
          fb = bars + B_FULL + (ring & ~7u);
          mbar_expect_tx(fb, STAGE);
          const uint32_t dst = sb + ((ring & ~7u) << 12);
          ring = rnext(ring);
          return dst;
        };
        if (lane == 0) {
          PROF(2, 0);
          const int cg = pair >> 3, g0 = ((pair & 7) * 2 + (int)rank) * 2;
#pragma unroll 1
          for (int t = 0; t < 12; t++) {
#pragma unroll 1
            for (int w = 0; w < 2; w++) {
              if (t == 0) {
                for (int st = 0; st < 2; st++) {
                  const uint32_t dst = acquire();
                  for (int kh = 0; kh < 4; kh++) tma_load(dst + kh * 8192, &P.tm_ckv, (st * 4 + kh) * 64, (g0 + w) * 64, fb);
                }
              } else if (t == 8) {
                if (w == 0) { flag_wait(&g_flags.ln_done, (epoch + 1) * 256); fence_async_global(); PROF(2, 1); }
                for (int st = 0; st < 2; st++) {
                  const uint32_t dst = acquire();
                  bulk_load(dst, g_xn + (size_t)((g0 + w) * 8 + st * 4) * 8192, 32768, fb);
                }
              }
              if (w == 0) {
                const CUtensorMap* tw = t >= 8 ? &P.tm_wq : ((t & 1) ? &P.tm_wuv : &P.tm_wuk);
                const int col = proj_head(t, cg) * 128 + rank * 64;
                for (int c = 0; c < 4; c++) {
                  const uint32_t dst = acquire();
                  tma_load_mc(dst + rank * 16384, tw, col, c * 128, fb);
                }
                if (t == 0) { l2_prefetch(P.x + (size_t)blockIdx.x * 16 * DM, 16384); epoch = read_epoch(); }
              }
            }
          }
          const int h0 = pair >> 2;
          flag_wait(&g_flags.kv_done[h0], (epoch + 1) * 64);
          flag_wait(&g_flags.q_done[h0], (epoch + 1) * 32);
          fence_async_global();
          PROF(2, 2);
          const unsigned char* kb = g_kv + (size_t)h0 * 2 * 16 * 32768 + rank * 16384;
          auto kv_load = [&](const unsigned char* src) {
            const uint32_t dst = acquire();
            bulk_load_mc(dst + rank * 16384, src, 16384, fb);
          };
#pragma unroll 1
          for (int rd = 0; rd < 2; rd++) {
            const int h = h0 + 16 * rd;
            const unsigned char* vb = kb + 16 * 32768;
#pragma unroll 1
            for (int s = 0; s < 17; s++) {
              if (s == 0 || s == a) {
                const int jj = s == 0 ? jx : 7 - jx;
                const int gL = 4 * jj + 3 - (int)rank, gS = 4 * jj + (int)rank;
                const uint32_t dst = acquire();
                bulk_load(dst, g_qc + ((size_t)(s == 0 ? gL : gS) * 32 + h) * 16384, 16384, fb);
                bulk_load(dst + 16384, g_qc + ((size_t)(s == 0 ? gS : gL) * 32 + h) * 16384, 16384, fb);
              }
              if (s <= a) kv_load(kb + (size_t)s * 32768);
              if (s >= a) kv_load(kb + (size_t)(16 - s) * 32768);
              if (s == 0) {
                if (rd) kv_load(vb - (size_t)16 * 2 * 16 * 32768);
              } else {
                if (s - 1 <= a) kv_load(vb + (size_t)(s - 1) * 32768);
                if (s - 1 >= a) kv_load(vb + (size_t)(17 - s) * 32768);
              }
              if (rd == 0 && s == 8) {
                flag_wait(&g_flags.kv_done[h0 + 16], (epoch + 1) * 64);
                flag_wait(&g_flags.q_done[h0 + 16], (epoch + 1) * 32);
                fence_async_global();
                PROF(2, 3);
              }
            }
            if (rd) kv_load(vb);
            kb += (size_t)16 * 2 * 16 * 32768;
          }
        }
        epoch = __shfl_sync(0xffffffffu, epoch, 0);
        const int j = pair >> 3, nh = (pair >> 2) & 1, ks = pair & 3;
        auto op_head = [&](int t) { return t < 4 ? ks * 4 + t : 16 + 4 * ks + 2 * (t & 1) + (((j >> 2) ^ (t >> 1)) & 1); };
        int done = 0;
        while (done < 8) {
          const bool ok = lane >= 8 || flag_ok(&g_flags.ctx[j * 32 + op_head(lane & 7)][0], (epoch + 1) * 4);
          const unsigned miss = ~__ballot_sync(0xffffffffu, ok);
          const int upto = miss ? __ffs(miss) - 1 : 8;
          __syncwarp();
          if (upto > done) {
            if (lane == 0) {
              fence_async_global();
              PROF(2, 4 + done);
              for (int t = done; t < upto; t++) {
                const int hh = op_head(t);
                uint32_t dst = acquire();
                const unsigned char* src = g_qc + ((size_t)(4 * j + 2 * rank) * 32 + hh) * 16384;
                bulk_load(dst, src, 16384, fb);
                bulk_load(dst + 16384, src + (size_t)32 * 16384, 16384, fb);
                for (int bb = 0; bb < 2; bb++) {
                  dst = acquire();
                  tma_load_mc(dst + rank * 16384, &P.tm_wo, nh * 256 + ((2 * rank + ks) & 3) * 64, hh * 128 + bb * 64, fb);
                  tma_load_mc(dst + rank * 16384 + 8192, &P.tm_wo, nh * 256 + ((2 * rank + 1 + ks) & 3) * 64, hh * 128 + bb * 64, fb);
                }
              }
            }
            __syncwarp();
            done = upto;
          } else {
            __nanosleep(100);
          }
        }
      }
      if (lane == 0) mbar_arrive(bars + B_DONE);
    } else if (warp_id < 3) {
      const int w = warp_id - 1;
      const uint32_t stg = sb + SM_STG + w * 16384;
      if (!spare) {
        const int cg = pair >> 3, rb = (pair & 7) * 2 + (int)rank;
        __nanosleep(400);
        l2_prefetch((w ? P.w_uv : P.w_uk) + (size_t)(rb * 32 + lane) * 4096 + 2048 + cg * 256, 512);
#pragma unroll 1
        for (int t = 0; t < 16; t++) {
          unsigned char* dst;
          unsigned* flag;
          uint32_t half = 8192;
          if (t < 8) {
            const int h = proj_head(t, cg);
            dst = g_kv + ((size_t)(h * 2 + (t & 1)) * 16 + rb) * 32768 + w * 8192; half = 16384;
            flag = &g_flags.kv_done[h];
          } else if (t < 12) {
            const int h = proj_head(t, cg);
            dst = g_qc + ((size_t)(rb * 2 + w) * 32 + h) * 16384;
            flag = &g_flags.q_done[h];
          } else {
            const int h = (pair >> 2) + 16 * ((t >> 1) & 1), y = t & 1;
            const int jj = y ? 7 - jx : jx;
            const int g = 4 * jj + ((y == w) ? 3 - (int)rank : (int)rank);
            dst = g_qc + ((size_t)g * 32 + h) * 16384;
            flag = &g_flags.ctx[jj * 32 + h][0];
          }
          bar_sync(3 + w, 160);
          if (lane == 0) {
            bulk_store(dst, stg, 8192);
            bulk_store(dst + half, stg + 8192, 8192);
            bulk_commit();
            bulk_wait_read0();
            mbar_arrive(bars + B_STFREE + w * 8);
            bulk_wait0();
            fence_gpu();
            red_relaxed(flag, 1);
            if (t == 3) red_relaxed(&g_flags.ln_done, 1);
          }
          __syncwarp();
          if (t == 0) l2_prefetch((w ? P.w_uv : P.w_uk) + (size_t)(rb * 32 + lane) * 4096 + cg * 256, 512);
          if (t == 3) l2_prefetch(P.w_q + (size_t)(rb * 32 + lane) * 4096 + w * 2048 + cg * 256, 512);
          if (t == 14) l2_prefetch(P.w_o + (size_t)(blockIdx.x * 64 + w * 32 + lane) * 256, 512);
        }
      }
      if (lane == 0) mbar_arrive(bars + B_DONE);
    } else {
      if (lane == 0) {
        uint32_t t0 = clk32();
        while (!mbar_try(bars + B_DONE, 0)) { __nanosleep(100); if (clk32() - t0 > TIMEOUT_CLKS) __trap(); }
        red_relaxed(&g_flags.exit_cnt, 1);
      }
      __syncwarp();
    }
    cluster_arrive();
    cluster_wait();
  } else {
    asm volatile("setmaxnreg.inc.sync.aligned.u32 232;");
    Cons C;
    C.sb = sb; C.bars = bars; C.w = (warp_id - 4) >> 2; C.warp = warp_id & 3; C.lane = lane; C.rank = rank;
    C.ring = 0; C.stphase = 1; C.epoch = 0;
    C.ebase = mapa(bars + B_EMPTY, lane & 1);
    if (lane >= 2) C.ebase = 0;
    asm volatile("" : "+r"(C.ebase));
    PROFC(62);
    if (spare) {
      cluster_arrive();
      C.epoch = read_epoch();
      moe_phase(C, P, (pair - 64) * 2 + (int)rank, smem_raw + (sb - sraw));
    } else {
      if (C.w == 1) bar_arrive(1, 256);
      proj_phase(C, P);
      att_phase(C, a);
      op_phase(C, P, pair >> 3, (pair >> 2) & 1, pair & 3);
    }
    __syncwarp();
    if (lane == 0) mbar_arrive(bars + B_DONE);
    cluster_wait();
  }
}

typedef CUresult (*EncodeFn)(CUtensorMap*, CUtensorMapDataType, cuuint32_t, void*, const cuuint64_t*, const cuuint64_t*, const cuuint32_t*,
                             const cuuint32_t*, CUtensorMapInterleave, CUtensorMapSwizzle, CUtensorMapL2promotion, CUtensorMapFloatOOBfill);

void make_map(EncodeFn enc, CUtensorMap* tm, const void* ptr, int cols, int rows, int box_rows) {
  cuuint64_t dims[2] = {(cuuint64_t)cols, (cuuint64_t)rows};
  cuuint64_t strides[1] = {(cuuint64_t)cols * 2};
  cuuint32_t box[2] = {64, (cuuint32_t)box_rows};
  cuuint32_t es[2] = {1, 1};
  enc(tm, CU_TENSOR_MAP_DATA_TYPE_BFLOAT16, 2, const_cast<void*>(ptr), dims, strides, box, es, CU_TENSOR_MAP_INTERLEAVE_NONE,
      CU_TENSOR_MAP_SWIZZLE_128B, CU_TENSOR_MAP_L2_PROMOTION_L2_256B, CU_TENSOR_MAP_FLOAT_OOB_FILL_NONE);
}

}

extern "C" void kernel_launch(void* const* d_in, const int* in_sizes, int n_in, void* d_out, int out_size) {
  (void)in_sizes; (void)n_in; (void)out_size;
  static EncodeFn enc = nullptr;
  if (!enc) {
    void* fn = nullptr;
    cudaDriverEntryPointQueryResult qr;
    cudaGetDriverEntryPoint("cuTensorMapEncodeTiled", &fn, cudaEnableDefault, &qr);
    enc = (EncodeFn)fn;
    cudaFuncSetAttribute(mega_kernel, cudaFuncAttributeMaxDynamicSharedMemorySize, SMEM_BYTES);
  }
  Params P;
  make_map(enc, &P.tm_ckv, d_in[1], 512, 2048, 64);
  make_map(enc, &P.tm_wq, d_in[2], 4096, 512, 128);
  make_map(enc, &P.tm_wuk, d_in[3], 4096, 512, 128);
  make_map(enc, &P.tm_wuv, d_in[4], 4096, 512, 128);
  make_map(enc, &P.tm_wo, d_in[5], 512, 4096, 64);
  P.x = (const __nv_bfloat16*)d_in[0];
  P.w_q = (const __nv_bfloat16*)d_in[2];
  P.w_uk = (const __nv_bfloat16*)d_in[3];
  P.w_uv = (const __nv_bfloat16*)d_in[4];
  P.w_o = (const __nv_bfloat16*)d_in[5];
  P.w_r = (const __nv_bfloat16*)d_in[7];
  P.w_gate = (const __nv_bfloat16*)d_in[8];
  P.w_up = (const __nv_bfloat16*)d_in[9];
  P.w_down = (const __nv_bfloat16*)d_in[10];
  P.out = (__nv_bfloat16*)d_out;
  cudaLaunchConfig_t cfg = {};
  cfg.gridDim = dim3(NCTA); cfg.blockDim = dim3(384); cfg.dynamicSmemBytes = SMEM_BYTES; cfg.stream = cudaStreamPerThread;
  cudaLaunchAttribute at[1];
  at[0].id = cudaLaunchAttributeClusterDimension; at[0].val.clusterDim.x = 2; at[0].val.clusterDim.y = 1; at[0].val.clusterDim.z = 1;
  cfg.attrs = at; cfg.numAttrs = 1;
  cudaLaunchKernelEx(&cfg, mega_kernel, P);
}
```

```cpp
#include <cuda_runtime.h>
#include <cuda_bf16.h>
#include <cuda.h>
#include <stdint.h>
#include <limits.h>
#include <type_traits>

namespace {

constexpr int DM = 512, NH = 32, FF = 1792;
constexpr int NCTA = 132;
constexpr int NST = 6;
constexpr uint32_t STAGE = 32768;
constexpr uint32_t SM_STG = NST * STAGE;
constexpr uint32_t SM_BAR = SM_STG + 32768;
constexpr uint32_t SMEM_BYTES = SM_BAR + 256 + 1024;
constexpr float QSCALE = 0.08838834764831845f * 1.4426950408889634f;
constexpr uint32_t B_FULL = 0, B_EMPTY = 64, B_STFREE = 128, B_DONE = 144;

struct alignas(64) Params {
  CUtensorMap tm_ckv, tm_wq, tm_wuk, tm_wuv, tm_wo;
  const __nv_bfloat16 *x, *w_q, *w_uk, *w_uv, *w_o, *w_r, *w_gate, *w_up, *w_down;
  __nv_bfloat16* out;
  uint32_t zero;
};

struct Flags {
  unsigned long long key[2]; unsigned pad0[28];
  unsigned exit_cnt; unsigned pad1[31];
  unsigned ln_done; unsigned pad2[31];
  unsigned moe_done; unsigned pad3[31];
  unsigned moe_fin; unsigned pad4[31];
  unsigned kv_done[32];
  unsigned q_done[32];
  unsigned ctx[256][8];
};

__device__ Flags g_flags;
__device__ __align__(1024) unsigned char g_kv[(size_t)NH * 2 * 16 * 32768];
__device__ __align__(1024) unsigned char g_xn[(size_t)32 * 8 * 8192];
__device__ __align__(1024) unsigned char g_qc[(size_t)32 * NH * 16384];
__device__ __align__(1024) uint4 g_exch[(size_t)16 * 4 * 3 * 4 * 512];
__device__ float g_ypart[4 * DM];
__device__ __align__(16) uint32_t g_selrow[DM / 2];

__device__ __forceinline__ uint32_t smem_u32(const void* p) { return (uint32_t)__cvta_generic_to_shared(p); }
__device__ __forceinline__ void mbar_init(uint32_t bar, int cnt) {
  asm volatile("mbarrier.init.shared::cta.b64 [%0], %1;" ::"r"(bar), "r"(cnt) : "memory");
}
__device__ __forceinline__ void mbar_expect_tx(uint32_t bar, uint32_t bytes) {
  asm volatile("mbarrier.arrive.expect_tx.shared::cta.b64 _, [%0], %1;" ::"r"(bar), "r"(bytes) : "memory");
}
__device__ __forceinline__ void mbar_arrive(uint32_t bar) {
  asm volatile("mbarrier.arrive.shared::cta.b64 _, [%0];" ::"r"(bar) : "memory");
}
__device__ __forceinline__ uint32_t mapa(uint32_t addr, uint32_t cta) {
  uint32_t r; asm volatile("mapa.shared::cluster.u32 %0, %1, %2;" : "=r"(r) : "r"(addr), "r"(cta)); return r;
}
__device__ __forceinline__ void mbar_arrive_cluster(uint32_t bar, uint32_t cnt) {
  asm volatile("mbarrier.arrive.shared::cluster.b64 _, [%0], %1;" ::"r"(bar), "r"(cnt) : "memory");
}
__device__ __forceinline__ uint32_t mbar_test2(uint32_t b0, uint32_t p0, uint32_t b1, uint32_t p1) {
  uint32_t ok;
  asm volatile("{\n.reg .pred p, q;\nmbarrier.test_wait.parity.shared::cta.b64 p, [%1], %2;\nmbarrier.test_wait.parity.shared::cta.b64 q, [%3], %4;\n"
               "and.pred p, p, q;\nselp.u32 %0, 1, 0, p;\n}\n" : "=r"(ok) : "r"(b0), "r"(p0), "r"(b1), "r"(p1) : "memory");
  return ok;
}
__device__ __forceinline__ bool mbar_try(uint32_t bar, uint32_t parity) {
  uint32_t ok;
  asm volatile("{\n.reg .pred p;\nmbarrier.try_wait.parity.shared::cta.b64 p, [%1], %2;\nselp.u32 %0, 1, 0, p;\n}\n"
               : "=r"(ok) : "r"(bar), "r"(parity) : "memory");
  return ok != 0;
}
__device__ __forceinline__ uint32_t clk32() { uint32_t c; asm volatile("mov.u32 %0, %%clock;" : "=r"(c)); return c; }
constexpr uint32_t TIMEOUT_CLKS = 1u << 30;
__device__ __forceinline__ void mbar_wait(uint32_t bar, uint32_t parity) {
  asm volatile("{\n.reg .pred p;\nWAIT_LOOP:\nmbarrier.try_wait.parity.shared::cta.b64 p, [%0], %1;\n@p bra WAIT_DONE;\nbra WAIT_LOOP;\nWAIT_DONE:\n}\n"
               ::"r"(bar), "r"(parity) : "memory");
}
__device__ __forceinline__ unsigned ld_acquire(const unsigned* p) {
  unsigned v; asm volatile("ld.acquire.gpu.global.u32 %0, [%1];" : "=r"(v) : "l"(p) : "memory"); return v;
}
__device__ __forceinline__ void red_release(unsigned* p, unsigned v) {
  asm volatile("red.release.gpu.global.add.u32 [%0], %1;" ::"l"(p), "r"(v) : "memory");
}
__device__ __forceinline__ void red_relaxed(unsigned* p, unsigned v) {
  asm volatile("red.relaxed.gpu.global.add.u32 [%0], %1;" ::"l"(p), "r"(v) : "memory");
}
__device__ __forceinline__ void st_relaxed128(uint4* p, uint32_t a, uint32_t b, uint32_t c, uint32_t d) {
  asm volatile("{\n.reg .b128 v;\nmov.b128 v, {%1,%2,%3,%4};\nst.relaxed.gpu.global.b128 [%0], v;\n}\n" ::"l"(p), "r"(a), "r"(b), "r"(c), "r"(d) : "memory");
}
__device__ __forceinline__ uint4 ld_relaxed128(const uint4* p) {
  uint4 v;
  asm volatile("{\n.reg .b128 v;\nld.relaxed.gpu.global.b128 v, [%4];\nmov.b128 {%0,%1,%2,%3}, v;\n}\n"
               : "=r"(v.x), "=r"(v.y), "=r"(v.z), "=r"(v.w) : "l"(p) : "memory");
  return v;
}
__device__ __forceinline__ unsigned ld_relaxed(const unsigned* p) {
  unsigned v; asm volatile("ld.relaxed.gpu.global.u32 %0, [%1];" : "=r"(v) : "l"(p) : "memory"); return v;
}
__device__ __forceinline__ bool flag_ok(const unsigned* p, unsigned target) { return (int)(ld_acquire(p) - target) >= 0; }
__device__ __forceinline__ void flag_wait(const unsigned* p, unsigned target) {
  while (!flag_ok(p, target)) { __nanosleep(40); }
}
__device__ __forceinline__ void fence_gpu() { asm volatile("fence.acq_rel.gpu;" ::: "memory"); }
__device__ __forceinline__ void fence_async_global() { asm volatile("fence.proxy.async.global;" ::: "memory"); }
__device__ __forceinline__ void fence_async_smem() { asm volatile("fence.proxy.async.shared::cta;" ::: "memory"); }
__device__ __forceinline__ void bar_sync(int id, int n) { asm volatile("bar.sync %0, %1;" ::"r"(id), "r"(n) : "memory"); }
__device__ __forceinline__ void bar_arrive(int id, int n) { asm volatile("bar.arrive %0, %1;" ::"r"(id), "r"(n) : "memory"); }

__device__ __forceinline__ void bulk_load(uint32_t dst, const void* src, uint32_t bytes, uint32_t bar) {
  asm volatile("cp.async.bulk.shared::cluster.global.mbarrier::complete_tx::bytes [%0], [%1], %2, [%3];"
               ::"r"(dst), "l"(src), "r"(bytes), "r"(bar) : "memory");
}
__device__ __forceinline__ void bulk_load_mc(uint32_t dst, const void* src, uint32_t bytes, uint32_t bar) {
  asm volatile("cp.async.bulk.shared::cluster.global.mbarrier::complete_tx::bytes.multicast::cluster [%0], [%1], %2, [%3], %4;"
               ::"r"(dst), "l"(src), "r"(bytes), "r"(bar), "h"((uint16_t)3) : "memory");
}
__device__ __forceinline__ void tma_load(uint32_t dst, const CUtensorMap* tm, int c0, int c1, uint32_t bar) {
  asm volatile("cp.async.bulk.tensor.2d.shared::cluster.global.mbarrier::complete_tx::bytes [%0], [%1, {%3, %4}], [%2];"
               ::"r"(dst), "l"(tm), "r"(bar), "r"(c0), "r"(c1) : "memory");
}
__device__ __forceinline__ void tma_load_mc(uint32_t dst, const CUtensorMap* tm, int c0, int c1, uint32_t bar) {
  asm volatile("cp.async.bulk.tensor.2d.shared::cluster.global.mbarrier::complete_tx::bytes.multicast::cluster [%0], [%1, {%3, %4}], [%2], %5;"
               ::"r"(dst), "l"(tm), "r"(bar), "r"(c0), "r"(c1), "h"((uint16_t)3) : "memory");
}
__device__ __forceinline__ void bulk_store(void* dst, uint32_t src, uint32_t bytes) {
  asm volatile("cp.async.bulk.global.shared::cta.bulk_group [%0], [%1], %2;" ::"l"(dst), "r"(src), "r"(bytes) : "memory");
}
__device__ __forceinline__ void bulk_commit() { asm volatile("cp.async.bulk.commit_group;" ::: "memory"); }
__device__ __forceinline__ void bulk_wait_read0() { asm volatile("cp.async.bulk.wait_group.read 0;" ::: "memory"); }
__device__ __forceinline__ void bulk_wait0() { asm volatile("cp.async.bulk.wait_group 0;" ::: "memory"); }
__device__ __forceinline__ void l2_prefetch(const void* p, uint32_t bytes) {
  asm volatile("cp.async.bulk.prefetch.L2.global [%0], %1;" ::"l"(p), "r"(bytes) : "memory");
}

#define WG_FENCE() asm volatile("wgmma.fence.sync.aligned;" ::: "memory")
#define WG_COMMIT() asm volatile("wgmma.commit_group.sync.aligned;" ::: "memory")
#define WG_WAIT(n) asm volatile("wgmma.wait_group.sync.aligned %0;" ::"n"(n) : "memory")

#define R8(a, o) "+f"(a[o + 0]), "+f"(a[o + 1]), "+f"(a[o + 2]), "+f"(a[o + 3]), "+f"(a[o + 4]), "+f"(a[o + 5]), "+f"(a[o + 6]), "+f"(a[o + 7])
#define R32(a, o) R8(a, o), R8(a, o + 8), R8(a, o + 16), R8(a, o + 24)
#define R64(a, o) R32(a, o), R32(a, o + 32)
#define ACC64 "{%0,%1,%2,%3,%4,%5,%6,%7,%8,%9,%10,%11,%12,%13,%14,%15,%16,%17,%18,%19,%20,%21,%22,%23,%24,%25,%26,%27,%28,%29,%30,%31," \
              "%32,%33,%34,%35,%36,%37,%38,%39,%40,%41,%42,%43,%44,%45,%46,%47,%48,%49,%50,%51,%52,%53,%54,%55,%56,%57,%58,%59,%60,%61,%62,%63}"

constexpr uint32_t DESC_HI = (1024u >> 4) | (1u << 30);
__device__ __forceinline__ uint32_t desc_lo(uint32_t addr, uint32_t lbo) { return ((addr & 0x3FFFFu) >> 4) | ((lbo >> 4) << 16); }

template <int TB>
__device__ __forceinline__ void mma_rs128(float (&d)[64], uint32_t a0, uint32_t a1, uint32_t a2, uint32_t a3, uint32_t blo, int acc) {
  asm volatile("{\n.reg .pred p;\n.reg .b64 db;\nsetp.ne.b32 p, %69, 0;\nmov.b64 db, {%68, %71};\n"
               "wgmma.mma_async.sync.aligned.m64n128k16.f32.bf16.bf16 " ACC64 ", {%64,%65,%66,%67}, db, p, 1, 1, %70;\n}\n"
               : R64(d, 0) : "r"(a0), "r"(a1), "r"(a2), "r"(a3), "r"(blo), "r"(acc), "n"(TB), "r"(DESC_HI));
}
__device__ __forceinline__ void mma_rs128_if(float (&d)[64], uint32_t a0, uint32_t a1, uint32_t a2, uint32_t a3, uint32_t blo, int acc, int on) {
  asm volatile("{\n.reg .pred p, q;\n.reg .b64 db;\nsetp.ne.b32 p, %69, 0;\nsetp.ne.b32 q, %70, 0;\nmov.b64 db, {%68, %71};\n"
               "@q wgmma.mma_async.sync.aligned.m64n128k16.f32.bf16.bf16 " ACC64 ", {%64,%65,%66,%67}, db, p, 1, 1, 1;\n}\n"
               : R64(d, 0) : "r"(a0), "r"(a1), "r"(a2), "r"(a3), "r"(blo), "r"(acc), "r"(on), "r"(DESC_HI));
}
__device__ __forceinline__ void mma_rs128_or64(float (&d)[64], uint32_t a0, uint32_t a1, uint32_t a2, uint32_t a3, uint32_t blo, int acc, int narrow) {
  asm volatile("{\n.reg .pred p, q;\n.reg .b64 db;\nsetp.ne.b32 p, %69, 0;\nsetp.ne.b32 q, %70, 0;\nmov.b64 db, {%68, %71};\n"
               "@!q wgmma.mma_async.sync.aligned.m64n128k16.f32.bf16.bf16 " ACC64 ", {%64,%65,%66,%67}, db, p, 1, 1, 0;\n"
               "@q wgmma.mma_async.sync.aligned.m64n64k16.f32.bf16.bf16 "
               "{%0,%1,%2,%3,%4,%5,%6,%7,%8,%9,%10,%11,%12,%13,%14,%15,%16,%17,%18,%19,%20,%21,%22,%23,%24,%25,%26,%27,%28,%29,%30,%31},"
               " {%64,%65,%66,%67}, db, p, 1, 1, 0;\n}\n"
               : R64(d, 0) : "r"(a0), "r"(a1), "r"(a2), "r"(a3), "r"(blo), "r"(acc), "r"(narrow), "r"(DESC_HI));
}
__device__ __forceinline__ void mma_ss256(float (&d)[128], uint32_t alo, uint32_t blo, int acc) {
  asm volatile("{\n.reg .pred p;\n.reg .b64 da, db;\nsetp.ne.b32 p, %130, 0;\nmov.b64 da, {%128, %131};\nmov.b64 db, {%129, %131};\n"
               "wgmma.mma_async.sync.aligned.m64n256k16.f32.bf16.bf16 "
               "{%0,%1,%2,%3,%4,%5,%6,%7,%8,%9,%10,%11,%12,%13,%14,%15,%16,%17,%18,%19,%20,%21,%22,%23,%24,%25,%26,%27,%28,%29,%30,%31,"
               "%32,%33,%34,%35,%36,%37,%38,%39,%40,%41,%42,%43,%44,%45,%46,%47,%48,%49,%50,%51,%52,%53,%54,%55,%56,%57,%58,%59,%60,%61,%62,%63,"
               "%64,%65,%66,%67,%68,%69,%70,%71,%72,%73,%74,%75,%76,%77,%78,%79,%80,%81,%82,%83,%84,%85,%86,%87,%88,%89,%90,%91,%92,%93,%94,%95,"
               "%96,%97,%98,%99,%100,%101,%102,%103,%104,%105,%106,%107,%108,%109,%110,%111,%112,%113,%114,%115,%116,%117,%118,%119,%120,%121,%122,%123,%124,%125,%126,%127},"
               " da, db, p, 1, 1, 0, 1;\n}\n"
               : R64(d, 0), R64(d, 64) : "r"(alo), "r"(blo), "r"(acc), "r"(DESC_HI));
}
template <int N>
__device__ __forceinline__ void fence_regs(float (&d)[N]) {
#pragma unroll
  for (int i = 0; i < N; i++) asm volatile("" : "+f"(d[i])::"memory");
}
__device__ __forceinline__ uint32_t pack_bf16(float lo, float hi) {
  uint32_t r; asm("cvt.rn.bf16x2.f32 %0, %1, %2;" : "=r"(r) : "f"(hi), "f"(lo)); return r;
}
__device__ __forceinline__ float bf16_round(float v) { return __bfloat162float(__float2bfloat16_rn(v)); }
__device__ __forceinline__ float bf_lo(uint32_t v) { return __uint_as_float(v << 16); }
__device__ __forceinline__ float bf_hi(uint32_t v) { return __uint_as_float(v & 0xFFFF0000u); }
__device__ __forceinline__ float ex2(float x) { float y; asm("ex2.approx.ftz.f32 %0, %1;" : "=f"(y) : "f"(x)); return y; }
__device__ __forceinline__ void stmatrix4(uint32_t addr, uint32_t r0, uint32_t r1, uint32_t r2, uint32_t r3) {
  asm volatile("stmatrix.sync.aligned.m8n8.x4.shared.b16 [%0], {%1,%2,%3,%4};" ::"r"(addr), "r"(r0), "r"(r1), "r"(r2), "r"(r3) : "memory");
}
__device__ __forceinline__ void ldmatrix4(uint32_t addr, uint32_t& r0, uint32_t& r1, uint32_t& r2, uint32_t& r3) {
  asm volatile("ldmatrix.sync.aligned.m8n8.x4.shared.b16 {%0,%1,%2,%3}, [%4];" : "=r"(r0), "=r"(r1), "=r"(r2), "=r"(r3) : "r"(addr) : "memory");
}
__device__ __forceinline__ void mma_16816(float* c, const uint32_t* a, uint32_t b0, uint32_t b1) {
  asm volatile("mma.sync.aligned.m16n8k16.row.col.f32.bf16.bf16.f32 {%0,%1,%2,%3}, {%4,%5,%6,%7}, {%8,%9}, {%0,%1,%2,%3};"
               : "+f"(c[0]), "+f"(c[1]), "+f"(c[2]), "+f"(c[3]) : "r"(a[0]), "r"(a[1]), "r"(a[2]), "r"(a[3]), "r"(b0), "r"(b1));
}
__device__ __forceinline__ void cluster_arrive() { asm volatile("barrier.cluster.arrive.relaxed;" ::: "memory"); }
__device__ __forceinline__ void cluster_wait() { asm volatile("barrier.cluster.wait;" ::: "memory"); }

__device__ __forceinline__ uint32_t read_epoch() {
  uint32_t v; asm volatile("ld.relaxed.gpu.global.u32 %0, [%1];" : "=r"(v) : "l"(&g_flags.exit_cnt) : "memory");
  return v / NCTA;
}
__device__ __forceinline__ uint32_t rnext(uint32_t r) { r += 8; return r >= NST * 8 ? (r - NST * 8) ^ 1u : r; }

#define PROF(role, slot) do { } while (0)
#define PROFC(slot) do { } while (0)

struct Cons {
  uint32_t sb;
  uint32_t bars;
  int w;
  int warp;
  int lane;
  uint32_t rank;
  uint32_t ring;
  uint32_t stphase;
  uint32_t epoch;
  uint32_t ebase;
  uint32_t zero;
  __device__ __forceinline__ void wait_full(uint32_t r) { mbar_wait(bars + B_FULL + (r & ~7u), r & 1u); }
  __device__ __forceinline__ uint32_t stage_addr(uint32_t r) { return sb + ((r & ~7u) << 12); }
  __device__ __forceinline__ void release(uint32_t r, uint32_t n = 1) { if (ebase) mbar_arrive_cluster(ebase + (r & ~7u), n); }
  template <int N>
  __device__ __forceinline__ void release_after(const uint32_t* regs, uint32_t r, uint32_t n = 1) {
    uint32_t d = 0;
#pragma unroll
    for (int i = 0; i < N; i++) d ^= regs[4 * i];
    __syncwarp();
    if (ebase) mbar_arrive_cluster(ebase + (r & ~7u) + (d & zero), n);
  }
  __device__ __forceinline__ void turn_sync() { bar_sync(1 + w, 256); }
  __device__ __forceinline__ void turn_pass() { bar_arrive(2 - w, 256); }
  __device__ __forceinline__ uint32_t frag_off() {
    const int mat = lane >> 3;
    return (warp * 16 + (mat & 1) * 8 + (lane & 7)) * 128 + ((((mat >> 1) ^ lane) & 7) << 4);
  }
  __device__ __forceinline__ void stage_out(const float (&a)[64], float s0, float s1) {
    mbar_wait(bars + B_STFREE + w * 8, stphase); stphase ^= 1;
    const uint32_t base = sb + SM_STG + w * 16384 + frag_off();
#pragma unroll
    for (int jj = 0; jj < 8; jj++) {
      const uint32_t r0 = pack_bf16(a[8 * jj + 0] * s0, a[8 * jj + 1] * s0), r1 = pack_bf16(a[8 * jj + 2] * s1, a[8 * jj + 3] * s1);
      const uint32_t r2 = pack_bf16(a[8 * jj + 4] * s0, a[8 * jj + 5] * s0), r3 = pack_bf16(a[8 * jj + 6] * s1, a[8 * jj + 7] * s1);
      stmatrix4((base ^ (((2 * jj) & 7) << 4)) + (jj >> 2) * 8192, r0, r1, r2, r3);
    }
    fence_async_smem();
    bar_arrive(3 + w, 160);
  }
};

__device__ __forceinline__ void ln_row(const Params& P, int row, int lane, uint32_t epoch) {
  uint4 v[2], wr[2];
  const uint4* xr = reinterpret_cast<const uint4*>(P.x + (size_t)row * DM);
  v[0] = __ldg(xr + lane); v[1] = __ldg(xr + lane + 32);
  wr[0] = __ldg(reinterpret_cast<const uint4*>(P.w_r) + lane); wr[1] = __ldg(reinterpret_cast<const uint4*>(P.w_r) + lane + 32);
  float f[16];
#pragma unroll
  for (int c = 0; c < 2; c++) {
    const uint32_t u[4] = {v[c].x, v[c].y, v[c].z, v[c].w};
#pragma unroll
    for (int e = 0; e < 4; e++) { f[c * 8 + 2 * e] = bf_lo(u[e]); f[c * 8 + 2 * e + 1] = bf_hi(u[e]); }
  }
  float s = 0.f;
#pragma unroll
  for (int e = 0; e < 16; e++) s += f[e];
#pragma unroll
  for (int o = 16; o > 0; o >>= 1) s += __shfl_xor_sync(0xffffffffu, s, o);
  const float mean = s * (1.0f / DM);
  float q = 0.f;
#pragma unroll
  for (int e = 0; e < 16; e++) { float d = f[e] - mean; q += d * d; }
#pragma unroll
  for (int o = 16; o > 0; o >>= 1) q += __shfl_xor_sync(0xffffffffu, q, o);
  const float m = bf16_round(mean);
  const float var = bf16_round(q * (1.0f / DM));
  const float rs = 1.0f / bf16_round(sqrtf(bf16_round(var + 1e-5f)));
  float r = 0.f;
  const int g = row >> 6, rl = row & 63;
#pragma unroll
  for (int c = 0; c < 2; c++) {
    const uint32_t wu[4] = {wr[c].x, wr[c].y, wr[c].z, wr[c].w};
    uint32_t o[4];
#pragma unroll
    for (int e = 0; e < 4; e++) {
      const uint32_t d = pack_bf16(f[c * 8 + 2 * e] - m, f[c * 8 + 2 * e + 1] - m);
      o[e] = pack_bf16(bf_lo(d) * rs, bf_hi(d) * rs);
      r += bf_lo(o[e]) * bf_lo(wu[e]); r += bf_hi(o[e]) * bf_hi(wu[e]);
    }
    const int c8 = lane + 32 * c, kh = c8 >> 3, ch = c8 & 7;
    *reinterpret_cast<uint4*>(g_xn + ((size_t)(g * 8 + kh) * 64 + rl) * 128 + ((ch ^ (rl & 7)) << 4)) = make_uint4(o[0], o[1], o[2], o[3]);
  }
#pragma unroll
  for (int o = 16; o > 0; o >>= 1) r += __shfl_xor_sync(0xffffffffu, r, o);
  uint32_t u = __float_as_uint(bf16_round(r) + 0.0f);
  u = (u & 0x80000000u) ? ~u : (u | 0x80000000u);
  const unsigned long long key = ((unsigned long long)u << 32) | (unsigned long long)(0xFFFFFFFFu - (uint32_t)row);
  if (lane == 0) asm volatile("red.relaxed.gpu.global.max.u64 [%0], %1;" ::"l"(&g_flags.key[epoch & 1]), "l"(key) : "memory");
}

__device__ __forceinline__ void proj_phase(Cons& C, const Params& P) {
  uint32_t af[128];
  float acc[64];
#pragma unroll 1
  for (int ph = 0; ph < 2; ph++) {
    {
      uint32_t r = C.ring;
      if (C.w == 0) { C.wait_full(r); C.wait_full(rnext(r)); bar_arrive(8, 256); }
      else { bar_sync(8, 256); r ^= 1u; }
      const uint32_t off = C.frag_off();
#pragma unroll
      for (int st = 0; st < 2; st++) {
        C.wait_full(r);
        const uint32_t base = C.stage_addr(r) + off;
#pragma unroll
        for (int kk = 0; kk < 16; kk++)
          ldmatrix4((base ^ ((2 * (kk & 3)) << 4)) + (kk >> 2) * 8192, af[st * 64 + kk * 4], af[st * 64 + kk * 4 + 1], af[st * 64 + kk * 4 + 2],
                    af[st * 64 + kk * 4 + 3]);
        C.release_after<16>(af + st * 64, r, 2);
        r = rnext(r);
      }
      C.ring = rnext(rnext(C.ring));
    }
    const int nt = ph ? 4 : 8;
#pragma unroll 1
    for (int t = 0; t < nt; t++) {
      uint32_t prev = 0;
      C.turn_sync();
#pragma unroll
      for (int c = 0; c < 4; c++) {
        C.wait_full(C.ring);
        const uint32_t blo = desc_lo(C.stage_addr(C.ring), 16384);
        WG_FENCE();
#pragma unroll
        for (int kk = 0; kk < 8; kk++)
          mma_rs128<1>(acc, af[c * 32 + kk * 4], af[c * 32 + kk * 4 + 1], af[c * 32 + kk * 4 + 2], af[c * 32 + kk * 4 + 3], blo + kk * 128,
                       (c | kk) != 0);
        WG_COMMIT();
        if (c == 3) C.turn_pass();
        if (c > 0) { WG_WAIT(1); C.release(prev); }
        prev = C.ring;
        C.ring = rnext(C.ring);
      }
      if (t == 0) C.ring = rnext(rnext(C.ring));
      WG_WAIT(0);
      C.release(prev);
      fence_regs(acc);
      const float sc = ph ? QSCALE : 1.0f;
      C.stage_out(acc, sc, sc);
      PROFC(ph * 8 + t);
      if (ph == 0) {
        if (t == 0) C.epoch = read_epoch();
        if (t == 1 || t == 2) ln_row(P, blockIdx.x * 16 + (C.w * 4 + C.warp) * 2 + t - 1, C.lane, C.epoch);
      }
    }
  }
}

__device__ __forceinline__ void att_phase(Cons& C, const int a) {
  constexpr int P1 = 9;
  float s[64], o[64];
  uint32_t q[32], p[32];
#pragma unroll
  for (int i = 0; i < 64; i++) o[i] = 0.f;
#pragma unroll
  for (int i = 0; i < 32; i++) p[i] = 0u;
  const uint32_t qoff = C.w * 16384 + C.frag_off();
  auto load_q = [&](uint32_t r) {
    C.wait_full(r);
    const uint32_t base = C.stage_addr(r) + qoff;
#pragma unroll
    for (int kk = 0; kk < 8; kk++) ldmatrix4((base ^ ((2 * (kk & 3)) << 4)) + (kk >> 2) * 8192, q[4 * kk], q[4 * kk + 1], q[4 * kk + 2], q[4 * kk + 3]);
    C.release_after<8>(q, r);
  };
  uint32_t ring = C.ring, qr = ring, kr, vr = 0;
  load_q(qr);
  ring = rnext(ring);
  kr = ring; ring = rnext(ring);
  C.wait_full(kr);
  const int sw = a + (int)C.rank;
  const int lim = C.w * 64 + C.warp * 16 + (C.lane >> 2) - 2 * (C.lane & 3);
  float m0 = 0.f, m1 = 0.f, l0 = 1.f, l1 = 1.f, a0 = 1.f, a1 = 1.f, t0, t1;
  bool usem = false, bad, half = false;
  uint32_t ready, hk;
  int st = 0, gs = 0, pvacc = 0;
  auto step = [&](auto fast_tag) {
    constexpr bool FAST = decltype(fast_tag)::value;
    const uint32_t klo = desc_lo(C.stage_addr(kr), 16), vlo = desc_lo(C.stage_addr(vr), 16384);
    const bool first = !FAST && (st == 0 || st == sw), last = !FAST && gs == 33;
    const bool diag = !FAST && (st == sw - 1 || st == sw);
    C.turn_sync();
    WG_FENCE();
#pragma unroll
    for (int kk = 0; kk < 8; kk++)
      mma_rs128<0>(s, q[4 * kk], q[4 * kk + 1], q[4 * kk + 2], q[4 * kk + 3], klo + (((kk >> 2) * 16384 + (kk & 3) * 32) >> 4), kk != 0);
    WG_COMMIT();
    if (FAST || gs > 0) {
      if (!FAST) WG_FENCE();
#pragma unroll
      for (int kk = 0; kk < 8; kk++) mma_rs128<1>(o, p[4 * kk], p[4 * kk + 1], p[4 * kk + 2], p[4 * kk + 3], vlo + kk * 128, kk ? 1 : pvacc);
      WG_COMMIT();
    } else {
      WG_COMMIT();
    }
    C.turn_pass();
    const uint32_t ck = kr, cv = vr;
    if (FAST) {
      kr = ring; vr = rnext(kr); ring = rnext(vr);
    } else {
      if (st == a - 1 || (st == 16 && !last)) { qr = ring; ring = rnext(ring); }
      if (!last) { kr = ring; ring = rnext(ring); }
      vr = ring; ring = rnext(ring);
      if (last) kr = vr;
      half = diag && C.w == 0;
      if (first) {
        l0 += __shfl_xor_sync(0xffffffffu, l0, 1); l1 += __shfl_xor_sync(0xffffffffu, l1, 1);
        l0 += __shfl_xor_sync(0xffffffffu, l0, 2); l1 += __shfl_xor_sync(0xffffffffu, l1, 2);
        a0 = __fdividef(1.0f, l0); a1 = __fdividef(1.0f, l1);
        l0 = 0.f; l1 = 0.f; m0 = 0.f; m1 = 0.f; usem = false;
      }
    }
    WG_WAIT(1);
    fence_regs(s);
    hk = ck;
    if (diag) {
#pragma unroll
      for (int i = 0; i < 16; i++) {
        if (8 * i > lim) s[4 * i] = -INFINITY;
        if (8 * i + 1 > lim) s[4 * i + 1] = -INFINITY;
        if (8 * i - 8 > lim) s[4 * i + 2] = -INFINITY;
        if (8 * i - 7 > lim) s[4 * i + 3] = -INFINITY;
      }
    }
    if (__builtin_expect(usem, 0)) {
#pragma unroll
      for (int i = 0; i < 16; i++) { s[4 * i] -= m0; s[4 * i + 1] -= m0; s[4 * i + 2] -= m1; s[4 * i + 3] -= m1; }
    }
#pragma unroll
    for (int i = 0; i < P1; i++) {
      s[4 * i] = ex2(s[4 * i]); s[4 * i + 1] = ex2(s[4 * i + 1]); s[4 * i + 2] = ex2(s[4 * i + 2]); s[4 * i + 3] = ex2(s[4 * i + 3]);
      if (i == 0) { t0 = s[0] + s[1]; t1 = s[2] + s[3]; }
      else { t0 += s[4 * i] + s[4 * i + 1]; t1 += s[4 * i + 2] + s[4 * i + 3]; }
    }
    if (__builtin_expect(!(t0 + t1 <= 0x1p30f), 0)) C.wait_full(kr);
    WG_WAIT(0);
    fence_regs(o);
    if (FAST || gs > 0) {
      C.release(cv);
      if (first) C.stage_out(o, a0, a1);
    }
    ready = mbar_test2(C.bars + B_FULL + (kr & ~7u), kr & 1u, C.bars + B_FULL + (vr & ~7u), vr & 1u);
#pragma unroll
    for (int i = 0; i < 16; i++) {
      if (i >= P1) {
        s[4 * i] = ex2(s[4 * i]); s[4 * i + 1] = ex2(s[4 * i + 1]); s[4 * i + 2] = ex2(s[4 * i + 2]); s[4 * i + 3] = ex2(s[4 * i + 3]);
        t0 += s[4 * i] + s[4 * i + 1]; t1 += s[4 * i + 2] + s[4 * i + 3];
      }
      p[2 * i] = pack_bf16(s[4 * i], s[4 * i + 1]); p[2 * i + 1] = pack_bf16(s[4 * i + 2], s[4 * i + 3]);
    }
    bad = !(t0 <= 0x1p30f && t1 <= 0x1p30f);
    if (first) {
      float u0 = t0 + __shfl_xor_sync(0xffffffffu, t0, 1), u1 = t1 + __shfl_xor_sync(0xffffffffu, t1, 1);
      u0 += __shfl_xor_sync(0xffffffffu, u0, 2); u1 += __shfl_xor_sync(0xffffffffu, u1, 2);
      bad = bad || !(u0 >= 0x1p-30f && u1 >= 0x1p-30f);
    }
    pvacc = first ? 0 : 1;
  };
  const uint32_t special = 1u | (7u << (a - 1)) | (1u << 16);
  PROFC(12);
  auto tail = [&](auto fast_tag) {
    constexpr bool FAST = decltype(fast_tag)::value;
    if (__builtin_expect(__any_sync(0xffffffffu, bad), 0)) {
      const uint32_t kbase = C.stage_addr(hk) + ((C.lane >> 4) * 8 + (C.lane & 7)) * 128 + (((((C.lane >> 3) & 1) ^ C.lane) & 7) << 4);
      const int dlim = (st == sw - 1 || st == sw) ? lim : 1024;
      float n0 = -INFINITY, n1 = -INFINITY;
#pragma unroll 1
      for (int it = 0; it < 16; it++) {
        const int jp = it & 7;
        float c[8];
#pragma unroll
        for (int i = 0; i < 8; i++) c[i] = 0.f;
#pragma unroll
        for (int kk = 0; kk < 8; kk++) {
          uint32_t b0, b1, b2, b3;
          ldmatrix4((kbase ^ ((2 * (kk & 3)) << 4)) + (kk >> 2) * 16384 + jp * 2048, b0, b1, b2, b3);
          mma_16816(c, q + 4 * kk, b0, b1);
          mma_16816(c + 4, q + 4 * kk, b2, b3);
        }
#pragma unroll
        for (int i = 0; i < 8; i++) if (16 * jp + 8 * (i >> 2) + (i & 1) - 8 * ((i >> 1) & 1) > dlim) c[i] = -INFINITY;
        if (it < 8) {
          n0 = fmaxf(fmaxf(n0, fmaxf(c[0], c[1])), fmaxf(c[4], c[5])); n1 = fmaxf(fmaxf(n1, fmaxf(c[2], c[3])), fmaxf(c[6], c[7]));
          if (it == 7) {
            n0 = fmaxf(n0, __shfl_xor_sync(0xffffffffu, n0, 1)); n1 = fmaxf(n1, __shfl_xor_sync(0xffffffffu, n1, 1));
            n0 = fmaxf(n0, __shfl_xor_sync(0xffffffffu, n0, 2)); n1 = fmaxf(n1, __shfl_xor_sync(0xffffffffu, n1, 2));
            if (pvacc) {
              n0 = fmaxf(n0, m0); n1 = fmaxf(n1, m1);
              const float f0 = ex2(m0 - n0), f1 = ex2(m1 - n1);
              l0 *= f0; l1 *= f1;
#pragma unroll
              for (int i = 0; i < 16; i++) { o[4 * i] *= f0; o[4 * i + 1] *= f0; o[4 * i + 2] *= f1; o[4 * i + 3] *= f1; }
            }
            m0 = n0; m1 = n1; usem = true;
            t0 = 0.f; t1 = 0.f;
          }
        } else {
#pragma unroll
          for (int i = 0; i < 8; i++) c[i] = ex2(c[i] - ((i & 2) ? m1 : m0));
          t0 += (c[0] + c[1]) + (c[4] + c[5]); t1 += (c[2] + c[3]) + (c[6] + c[7]);
#pragma unroll
          for (int i = 0; i < 28; i++) p[i] = p[i + 4];
#pragma unroll
          for (int i = 0; i < 4; i++) p[28 + i] = pack_bf16(c[2 * i], c[2 * i + 1]);
        }
      }
      __syncwarp();
    }
    C.release(hk);
    l0 += t0; l1 += t1;
    st = (!FAST && st == 16) ? 0 : st + 1;
    if (!FAST && (st == sw || (st == 0 && gs != 33))) load_q(qr);
    if (!ready) { C.wait_full(kr); C.wait_full(vr); }
    PROFC(13 + gs);
    gs++;
  };
#pragma unroll 1
  while (gs < 34) {
    step(std::false_type()); tail(std::false_type());
#pragma unroll 1
    while (!((special >> st) & 1u)) { step(std::true_type()); tail(std::true_type()); }
  }
  {
    const uint32_t vlo = desc_lo(C.stage_addr(vr), 16384);
    C.turn_sync();
    WG_FENCE();
#pragma unroll
    for (int kk = 0; kk < 8; kk++) mma_rs128<1>(o, p[4 * kk], p[4 * kk + 1], p[4 * kk + 2], p[4 * kk + 3], vlo + kk * 128, kk ? 1 : pvacc);
    WG_COMMIT();
    if (C.w == 0) C.turn_pass();
    l0 += __shfl_xor_sync(0xffffffffu, l0, 1); l1 += __shfl_xor_sync(0xffffffffu, l1, 1);
    l0 += __shfl_xor_sync(0xffffffffu, l0, 2); l1 += __shfl_xor_sync(0xffffffffu, l1, 2);
    a0 = __fdividef(1.0f, l0); a1 = __fdividef(1.0f, l1);
    WG_WAIT(0);
    C.release(vr);
    fence_regs(o);
    C.stage_out(o, a0, a1);
    PROFC(47);
  }
  C.ring = ring;
}

__device__ __forceinline__ void op_phase(Cons& C, const Params& P, int j, int nh, int ks) {
  float acc[128];
#pragma unroll
  for (int i = 0; i < 128; i++) acc[i] = 0.f;
  uint32_t pa = 0, pb = 0;
  const int sel = (int)(0xFFFFFFFFu - (uint32_t)__ldcg(&g_flags.key[C.epoch & 1]));
  const int tid = C.warp * 32 + C.lane;
  const int g = 4 * j + 2 * (int)C.rank + C.w;
  const int kh = 4 * nh + ks;
  if ((sel >> 4) == g * 4 + C.warp) { flag_wait(&g_flags.moe_fin, C.epoch + 1); __syncwarp(); }
  uint4 xv[4], nv[4];
#pragma unroll
  for (int i = 0; i < 4; i++) {
    const int idx = C.warp * 128 + C.lane + 32 * i, row = idx >> 3, ch = (idx ^ row) & 7;
    xv[i] = __ldg(reinterpret_cast<const uint4*>(P.x + (size_t)(g * 64 + row) * DM + kh * 64 + ch * 8));
    const uint4* np = reinterpret_cast<const uint4*>(g_xn + (size_t)(g * 8 + kh) * 8192) + idx;
    if (g * 64 + row == sel) np = reinterpret_cast<const uint4*>(g_selrow) + kh * 8 + ch;
    nv[i] = __ldcg(np);
  }
#pragma unroll 1
  for (int t = 0; t < 8; t++) {
    const uint32_t ia = C.ring, i0 = rnext(ia), i1 = rnext(i0);
    C.ring = rnext(i1);
    C.wait_full(ia);
    const uint32_t alo = desc_lo(C.stage_addr(ia) + C.w * 16384, 16);
    C.wait_full(i0);
    const uint32_t b0 = desc_lo(C.stage_addr(i0), 8192);
    WG_FENCE();
#pragma unroll
    for (int kk = 0; kk < 4; kk++) mma_ss256(acc, alo + kk * 2, b0 + kk * 128, 1);
    WG_COMMIT();
    if (t > 0) { WG_WAIT(1); if (t < 7) { C.release(pa); C.release(pb); } }
    C.wait_full(i1);
    const uint32_t b1 = desc_lo(C.stage_addr(i1), 8192);
    WG_FENCE();
#pragma unroll
    for (int kk = 0; kk < 4; kk++) mma_ss256(acc, alo + 512 + kk * 2, b1 + kk * 128, 1);
    WG_COMMIT();
    WG_WAIT(1);
    if (t < 6) C.release(i0);
    pa = ia; pb = i1;
  }
  cluster_arrive();
  WG_WAIT(0);
  fence_regs(acc);
  PROFC(48);
  const int tile = j * 2 + nh, sub = (int)C.rank * 2 + C.w;
  const uint32_t tag = ~C.epoch & 1u;
#pragma unroll
  for (int pp = 1; pp < 4; pp++) {
    uint4* dst = g_exch + (size_t)(((tile * 4 + ((pp + ks) & 3)) * 3 + (pp - 1)) * 4 + sub) * 512 + tid;
#pragma unroll
    for (int v = 0; v < 4; v++) {
      const float* f = acc + 32 * pp + 8 * v;
      st_relaxed128(dst + v * 128, (pack_bf16(f[0], f[1]) & ~1u) | tag, pack_bf16(f[2], f[3]), pack_bf16(f[4], f[5]), pack_bf16(f[6], f[7]));
    }
  }
  __syncwarp();
  if (C.lane < 3) red_relaxed(&g_flags.ctx[(tile * 4 + ((C.lane + 1 + ks) & 3)) * 4 + sub][4 + C.warp], 1);
  PROFC(49);
  if (C.lane == 0) {
    const unsigned* hint = &g_flags.ctx[(tile * 4 + ks) * 4 + sub][4 + C.warp];
    while ((int)(ld_relaxed(hint) - (C.epoch + 1) * 3) < 0) {}
  }
  __syncwarp();
  PROFC(50);
  const uint4* src = g_exch + (size_t)((tile * 4 + ks) * 3 * 4 + sub) * 512 + tid;
  uint4 e[12];
#pragma unroll 1
  for (;;) {
    uint32_t any = 0, all = 1;
#pragma unroll
    for (int i = 0; i < 12; i++) e[i] = ld_relaxed128(src + (i >> 2) * 2048 + (i & 3) * 128);
#pragma unroll
    for (int i = 0; i < 12; i++) { any |= e[i].x; all &= e[i].x; }
    if (__all_sync(0xffffffffu, ((tag ? all : ~any) & 1u) != 0u)) break;
  }
  PROFC(52);
#pragma unroll
  for (int i = 0; i < 12; i++) {
    float* d = acc + 8 * (i & 3);
    d[0] += bf_lo(e[i].x); d[1] += bf_hi(e[i].x); d[2] += bf_lo(e[i].y); d[3] += bf_hi(e[i].y);
    d[4] += bf_lo(e[i].z); d[5] += bf_hi(e[i].z); d[6] += bf_lo(e[i].w); d[7] += bf_hi(e[i].w);
  }
  mbar_wait(C.bars + B_STFREE + C.w * 8, C.stphase);
  const uint32_t stg = C.sb + SM_STG + C.w * 16384;
  {
    const uint32_t base = stg + C.frag_off();
#pragma unroll
    for (int jj = 0; jj < 4; jj++)
      stmatrix4(base ^ ((2 * jj) << 4), pack_bf16(acc[8 * jj], acc[8 * jj + 1]), pack_bf16(acc[8 * jj + 2], acc[8 * jj + 3]),
                pack_bf16(acc[8 * jj + 4], acc[8 * jj + 5]), pack_bf16(acc[8 * jj + 6], acc[8 * jj + 7]));
  }
  __syncwarp();
  PROFC(54);
#pragma unroll
  for (int i = 0; i < 4; i++) {
    const int idx = C.warp * 128 + C.lane + 32 * i, row = idx >> 3, ch = (idx ^ row) & 7;
    uint4 av;
    asm volatile("ld.shared.v4.u32 {%0,%1,%2,%3}, [%4];" : "=r"(av.x), "=r"(av.y), "=r"(av.z), "=r"(av.w) : "r"(stg + idx * 16) : "memory");
    const uint32_t au[4] = {av.x, av.y, av.z, av.w}, xu[4] = {xv[i].x, xv[i].y, xv[i].z, xv[i].w}, nu[4] = {nv[i].x, nv[i].y, nv[i].z, nv[i].w};
    uint32_t ou[4];
#pragma unroll
    for (int e2 = 0; e2 < 4; e2++) {
      const uint32_t xa = pack_bf16(bf_lo(xu[e2]) + bf_lo(au[e2]), bf_hi(xu[e2]) + bf_hi(au[e2]));
      ou[e2] = pack_bf16(bf_lo(xa) + bf_lo(nu[e2]), bf_hi(xa) + bf_hi(nu[e2]));
    }
    *reinterpret_cast<uint4*>(P.out + (size_t)(g * 64 + row) * DM + kh * 64 + ch * 8) = make_uint4(ou[0], ou[1], ou[2], ou[3]);
  }
  PROFC(51);
}

__device__ __forceinline__ void moe_phase(Cons& C, const Params& P, int part, unsigned char* smem) {
  const int tid = C.w * 128 + C.warp * 32 + C.lane;
  float* xs = reinterpret_cast<float*>(smem + SM_STG);
  float* hs = xs + 512;
  float* red = xs + 1024;
  if (tid == 0) flag_wait(&g_flags.ln_done, (C.epoch + 1) * 256);
  bar_sync(5, 256);
  const unsigned long long key = __ldcg(&g_flags.key[C.epoch & 1]);
  const int sel = (int)(0xFFFFFFFFu - (uint32_t)key);
  {
    const int g = sel >> 6, rl = sel & 63;
    const int c2 = tid * 2, kh = c2 >> 6, ch = (c2 >> 3) & 7;
    const uint32_t u = __ldcg(reinterpret_cast<const uint32_t*>(g_xn + ((size_t)(g * 8 + kh) * 64 + rl) * 128 + ((ch ^ (rl & 7)) << 4) + (c2 & 7) * 2));
    xs[c2] = bf_lo(u); xs[c2 + 1] = bf_hi(u);
  }
  bar_sync(5, 256);
  if (tid < 224) {
    const int chunk = tid % 56, kg = tid / 56;
    const uint4* wg = reinterpret_cast<const uint4*>(P.w_gate + (size_t)kg * 128 * FF + part * 448 + chunk * 8);
    const uint4* wu = reinterpret_cast<const uint4*>(P.w_up + (size_t)kg * 128 * FF + part * 448 + chunk * 8);
    float ag[8], au[8];
#pragma unroll
    for (int e = 0; e < 8; e++) { ag[e] = 0.f; au[e] = 0.f; }
#pragma unroll 1
    for (int k0 = 0; k0 < 128; k0 += 16) {
      uint4 vg[16], vu[16];
#pragma unroll
      for (int i = 0; i < 16; i++) { vg[i] = __ldg(wg + (size_t)(k0 + i) * (FF / 8)); vu[i] = __ldg(wu + (size_t)(k0 + i) * (FF / 8)); }
#pragma unroll
      for (int i = 0; i < 16; i++) {
        const float xk = xs[kg * 128 + k0 + i];
        const uint32_t a[4] = {vg[i].x, vg[i].y, vg[i].z, vg[i].w}, b[4] = {vu[i].x, vu[i].y, vu[i].z, vu[i].w};
#pragma unroll
        for (int e = 0; e < 4; e++) {
          ag[2 * e] += xk * bf_lo(a[e]); ag[2 * e + 1] += xk * bf_hi(a[e]);
          au[2 * e] += xk * bf_lo(b[e]); au[2 * e + 1] += xk * bf_hi(b[e]);
        }
      }
    }
#pragma unroll
    for (int e = 0; e < 8; e++) { red[(kg * 2) * 448 + chunk * 8 + e] = ag[e]; red[(kg * 2 + 1) * 448 + chunk * 8 + e] = au[e]; }
  }
  bar_sync(5, 256);
  for (int f = tid; f < 448; f += 256) {
    float gs = 0.f, us = 0.f;
#pragma unroll
    for (int kg = 0; kg < 4; kg++) { gs += red[(kg * 2) * 448 + f]; us += red[(kg * 2 + 1) * 448 + f]; }
    gs = bf16_round(gs); us = bf16_round(us);
    const float sl = bf16_round(gs / (1.0f + expf(-gs)));
    hs[f] = bf16_round(sl * us);
  }
  bar_sync(5, 256);
  {
    const int chunk = tid & 63, rg = tid >> 6;
    const uint4* wd = reinterpret_cast<const uint4*>(P.w_down + (size_t)(part * 448 + rg * 112) * DM + chunk * 8);
    float ay[8];
#pragma unroll
    for (int e = 0; e < 8; e++) ay[e] = 0.f;
#pragma unroll 1
    for (int k0 = 0; k0 < 112; k0 += 28) {
      uint4 v[28];
#pragma unroll
      for (int i = 0; i < 28; i++) v[i] = __ldg(wd + (size_t)(k0 + i) * (DM / 8));
#pragma unroll
      for (int i = 0; i < 28; i++) {
        const float hk = hs[rg * 112 + k0 + i];
        const uint32_t a[4] = {v[i].x, v[i].y, v[i].z, v[i].w};
#pragma unroll
        for (int e = 0; e < 4; e++) { ay[2 * e] += hk * bf_lo(a[e]); ay[2 * e + 1] += hk * bf_hi(a[e]); }
      }
    }
#pragma unroll
    for (int e = 0; e < 8; e++) red[rg * 512 + chunk * 8 + e] = ay[e];
  }
  bar_sync(5, 256);
  for (int c = tid; c < DM; c += 256) g_ypart[part * DM + c] = red[c] + red[512 + c] + red[1024 + c] + red[1536 + c];
  bar_sync(5, 256);
  if (tid == 0) red_release(&g_flags.moe_done, 1);
  if (part == 0) {
    if (tid == 0) flag_wait(&g_flags.moe_done, (C.epoch + 1) * 4);
    bar_sync(5, 256);
    uint32_t ub = (uint32_t)(key >> 32);
    ub = (ub & 0x80000000u) ? (ub & 0x7FFFFFFFu) : ~ub;
    const float sig = bf16_round(1.0f / (1.0f + expf(-__uint_as_float(ub))));
    float y0 = 0.f, y1 = 0.f;
#pragma unroll
    for (int c = 0; c < 4; c++) { y0 += __ldcg(&g_ypart[c * DM + 2 * tid]); y1 += __ldcg(&g_ypart[c * DM + 2 * tid + 1]); }
    y0 = bf16_round(bf16_round(y0) * sig); y1 = bf16_round(bf16_round(y1) * sig);
    g_selrow[tid] = pack_bf16(xs[2 * tid] + y0, xs[2 * tid + 1] + y1);
    bar_sync(5, 256);
    if (tid == 0) red_release(&g_flags.moe_fin, 1);
  }
}

__device__ __forceinline__ int proj_head(int t, int cg) {
  if (t < 8) return (t < 4 ? 16 : 0) + 2 * cg + ((t >> 1) & 1);
  return (t < 10 ? 0 : 16) + 2 * cg + (t & 1);
}

__global__ void __launch_bounds__(384, 1) mega_kernel(const __grid_constant__ Params P) {
  extern __shared__ unsigned char smem_raw[];
  const uint32_t sraw = smem_u32(smem_raw);
  const uint32_t sb = (sraw + 1023u) & ~1023u;
  const uint32_t bars = sb + SM_BAR;
  const int warp_id = __shfl_sync(0xffffffffu, threadIdx.x >> 5, 0);
  const int lane = threadIdx.x & 31;
  uint32_t rank; asm volatile("mov.u32 %0, %%cluster_ctarank;" : "=r"(rank));
  const int pair = blockIdx.x >> 1;
  const bool spare = pair >= 64;
  const int jx = (pair & 3) + (pair & 4);
  const int a = 2 * jx + 1;

  if (threadIdx.x == 0) {
    for (int s = 0; s < NST; s++) { mbar_init(bars + B_FULL + s * 8, 1); mbar_init(bars + B_EMPTY + s * 8, 16); }
    mbar_init(bars + B_STFREE, 1); mbar_init(bars + B_STFREE + 8, 1);
    mbar_init(bars + B_DONE, 11);
    asm volatile("fence.mbarrier_init.release.cluster;" ::: "memory");
  }
  __syncthreads();
  asm volatile("barrier.cluster.arrive.relaxed.aligned;\nbarrier.cluster.wait.aligned;" ::: "memory");

  if (warp_id < 4) {
    asm volatile("setmaxnreg.dec.sync.aligned.u32 40;");
    if (warp_id == 0) {
      if (spare) {
        __nanosleep(4000);
        const int part = (pair - 64) * 2 + (int)rank;
        for (int i = lane; i < 512; i += 32) {
          l2_prefetch(P.w_gate + (size_t)i * FF + part * 448, 896);
          l2_prefetch(P.w_up + (size_t)i * FF + part * 448, 896);
        }
        if (lane < 28) l2_prefetch(P.w_down + (size_t)(part * 448 + lane * 16) * DM, 16384);
        if (blockIdx.x == 128 && lane == 0) g_flags.key[(read_epoch() + 1) & 1] = 0;
      } else {
        uint32_t ring = 1, fb = 0, epoch = 0;
        auto acquire = [&]() -> uint32_t {
          mbar_wait(bars + B_EMPTY + (ring & ~7u), ring & 1u);
          fb = bars + B_FULL + (ring & ~7u);
          mbar_expect_tx(fb, STAGE);
          const uint32_t dst = sb + ((ring & ~7u) << 12);
          ring = rnext(ring);
          return dst;
        };
        if (lane == 0) {
          PROF(2, 0);
          const int cg = pair >> 3, g0 = ((pair & 7) * 2 + (int)rank) * 2;
#pragma unroll 1
          for (int t = 0; t < 12; t++) {
#pragma unroll 1
            for (int w = 0; w < 2; w++) {
              if (t == 0) {
                for (int st = 0; st < 2; st++) {
                  const uint32_t dst = acquire();
                  for (int kh = 0; kh < 4; kh++) tma_load(dst + kh * 8192, &P.tm_ckv, (st * 4 + kh) * 64, (g0 + w) * 64, fb);
                }
              } else if (t == 8) {
                if (w == 0) { flag_wait(&g_flags.ln_done, (epoch + 1) * 256); fence_async_global(); PROF(2, 1); }
                for (int st = 0; st < 2; st++) {
                  const uint32_t dst = acquire();
                  bulk_load(dst, g_xn + (size_t)((g0 + w) * 8 + st * 4) * 8192, 32768, fb);
                }
              }
              if (w == 0) {
                const CUtensorMap* tw = t >= 8 ? &P.tm_wq : ((t & 1) ? &P.tm_wuv : &P.tm_wuk);
                const int col = proj_head(t, cg) * 128 + rank * 64;
                for (int c = 0; c < 4; c++) {
                  const uint32_t dst = acquire();
                  tma_load_mc(dst + rank * 16384, tw, col, c * 128, fb);
                }
                if (t == 0) { l2_prefetch(P.x + (size_t)blockIdx.x * 16 * DM, 16384); epoch = read_epoch(); }
              }
            }
          }
          const int h0 = pair >> 2;
          flag_wait(&g_flags.kv_done[h0], (epoch + 1) * 64);
          flag_wait(&g_flags.q_done[h0], (epoch + 1) * 32);
          fence_async_global();
          PROF(2, 2);
          const unsigned char* kb = g_kv + (size_t)h0 * 2 * 16 * 32768;
          auto kv_load = [&](const unsigned char* base, int s) {
            const uint32_t dst = acquire();
            if (s == a) bulk_load(dst, base + (size_t)(rank ? a : 16 - a) * 32768, 32768, fb);
            else bulk_load_mc(dst + rank * 16384, base + (size_t)(s < a ? s : 16 - s) * 32768 + rank * 16384, 16384, fb);
          };
#pragma unroll 1
          for (int rd = 0; rd < 2; rd++) {
            const int h = h0 + 16 * rd;
            const unsigned char* vb = kb + 16 * 32768;
#pragma unroll 1
            for (int s = 0; s < 17; s++) {
              if (s == 0 || s == a) {
                const int g = s == 0 ? 4 * jx + 2 * (int)rank : 4 * (7 - jx) + 2 - 2 * (int)rank;
                const uint32_t dst = acquire();
                bulk_load(dst, g_qc + ((size_t)g * 32 + h) * 16384, 16384, fb);
                bulk_load(dst + 16384, g_qc + ((size_t)g * 32 + 32 + h) * 16384, 16384, fb);
              }
              kv_load(kb, s);
              if (s) kv_load(vb, s - 1);
              else if (rd) kv_load(vb - (size_t)16 * 2 * 16 * 32768, 16);
              if (rd == 0 && s == 8) {
                flag_wait(&g_flags.kv_done[h0 + 16], (epoch + 1) * 64);
                flag_wait(&g_flags.q_done[h0 + 16], (epoch + 1) * 32);
                fence_async_global();
                PROF(2, 3);
              }
            }
            if (rd) kv_load(vb, 16);
            kb += (size_t)16 * 2 * 16 * 32768;
          }
        }
        epoch = __shfl_sync(0xffffffffu, epoch, 0);
        const int j = pair >> 3, nh = (pair >> 2) & 1, ks = pair & 3;
        auto op_head = [&](int t) { return t < 4 ? ks * 4 + t : 16 + 4 * ks + 2 * (t & 1) + (((j >> 2) ^ (t >> 1)) & 1); };
        int done = 0;
        while (done < 8) {
          const bool ok = lane >= 8 || flag_ok(&g_flags.ctx[j * 32 + op_head(lane & 7)][0], (epoch + 1) * 4);
          const unsigned miss = ~__ballot_sync(0xffffffffu, ok);
          const int upto = miss ? __ffs(miss) - 1 : 8;
          __syncwarp();
          if (upto > done) {
            if (lane == 0) {
              fence_async_global();
              PROF(2, 4 + done);
              for (int t = done; t < upto; t++) {
                const int hh = op_head(t);
                uint32_t dst = acquire();
                const unsigned char* src = g_qc + ((size_t)(4 * j + 2 * rank) * 32 + hh) * 16384;
                bulk_load(dst, src, 16384, fb);
                bulk_load(dst + 16384, src + (size_t)32 * 16384, 16384, fb);
                for (int bb = 0; bb < 2; bb++) {
                  dst = acquire();
                  tma_load_mc(dst + rank * 16384, &P.tm_wo, nh * 256 + ((2 * rank + ks) & 3) * 64, hh * 128 + bb * 64, fb);
                  tma_load_mc(dst + rank * 16384 + 8192, &P.tm_wo, nh * 256 + ((2 * rank + 1 + ks) & 3) * 64, hh * 128 + bb * 64, fb);
                }
              }
            }
            __syncwarp();
            done = upto;
          } else {
            __nanosleep(100);
          }
        }
      }
      if (lane == 0) mbar_arrive(bars + B_DONE);
    } else if (warp_id < 3) {
      const int w = warp_id - 1;
      const uint32_t stg = sb + SM_STG + w * 16384;
      if (!spare) {
        const int cg = pair >> 3, rb = (pair & 7) * 2 + (int)rank;
        __nanosleep(400);
        l2_prefetch((w ? P.w_uv : P.w_uk) + (size_t)(rb * 32 + lane) * 4096 + 2048 + cg * 256, 512);
#pragma unroll 1
        for (int t = 0; t < 16; t++) {
          unsigned char* dst;
          unsigned* flag;
          uint32_t half = 8192;
          if (t < 8) {
            const int h = proj_head(t, cg);
            dst = g_kv + ((size_t)(h * 2 + (t & 1)) * 16 + rb) * 32768 + w * 8192; half = 16384;
            flag = &g_flags.kv_done[h];
          } else if (t < 12) {
            const int h = proj_head(t, cg);
            dst = g_qc + ((size_t)(rb * 2 + w) * 32 + h) * 16384;
            flag = &g_flags.q_done[h];
          } else {
            const int h = (pair >> 2) + 16 * ((t >> 1) & 1), y = t & 1;
            const int jj = y ? 7 - jx : jx;
            const int g = 4 * jj + 2 * (y ^ (int)rank) + w;
            dst = g_qc + ((size_t)g * 32 + h) * 16384;
            flag = &g_flags.ctx[jj * 32 + h][0];
          }
          bar_sync(3 + w, 160);
          if (lane == 0) {
            bulk_store(dst, stg, 8192);
            bulk_store(dst + half, stg + 8192, 8192);
            bulk_commit();
            bulk_wait_read0();
            mbar_arrive(bars + B_STFREE + w * 8);
            bulk_wait0();
            fence_gpu();
            red_relaxed(flag, 1);
            if (t == 3) red_relaxed(&g_flags.ln_done, 1);
          }
          __syncwarp();
          if (t == 0) l2_prefetch((w ? P.w_uv : P.w_uk) + (size_t)(rb * 32 + lane) * 4096 + cg * 256, 512);
          if (t == 3) l2_prefetch(P.w_q + (size_t)(rb * 32 + lane) * 4096 + w * 2048 + cg * 256, 512);
          if (t == 14) l2_prefetch(P.w_o + (size_t)(blockIdx.x * 64 + w * 32 + lane) * 256, 512);
        }
      }
      if (lane == 0) mbar_arrive(bars + B_DONE);
    } else {
      if (lane == 0) {
        uint32_t t0 = clk32();
        while (!mbar_try(bars + B_DONE, 0)) { __nanosleep(100); if (clk32() - t0 > TIMEOUT_CLKS) __trap(); }
        red_relaxed(&g_flags.exit_cnt, 1);
      }
      __syncwarp();
    }
    cluster_arrive();
    cluster_wait();
  } else {
    asm volatile("setmaxnreg.inc.sync.aligned.u32 232;");
    Cons C;
    C.sb = sb; C.bars = bars; C.w = (warp_id - 4) >> 2; C.warp = warp_id & 3; C.lane = lane; C.rank = rank;
    C.ring = 0; C.stphase = 1; C.epoch = 0; C.zero = P.zero;
    C.ebase = mapa(bars + B_EMPTY, lane & 1);
    if (lane >= 2) C.ebase = 0;
    asm volatile("" : "+r"(C.ebase));
    PROFC(62);
    if (spare) {
      cluster_arrive();
      C.epoch = read_epoch();
      moe_phase(C, P, (pair - 64) * 2 + (int)rank, smem_raw + (sb - sraw));
    } else {
      if (C.w == 1) bar_arrive(1, 256);
      proj_phase(C, P);
      att_phase(C, a);
      op_phase(C, P, pair >> 3, (pair >> 2) & 1, pair & 3);
    }
    __syncwarp();
    if (lane == 0) mbar_arrive(bars + B_DONE);
    cluster_wait();
  }
}

typedef CUresult (*EncodeFn)(CUtensorMap*, CUtensorMapDataType, cuuint32_t, void*, const cuuint64_t*, const cuuint64_t*, const cuuint32_t*,
                             const cuuint32_t*, CUtensorMapInterleave, CUtensorMapSwizzle, CUtensorMapL2promotion, CUtensorMapFloatOOBfill);

void make_map(EncodeFn enc, CUtensorMap* tm, const void* ptr, int cols, int rows, int box_rows) {
  cuuint64_t dims[2] = {(cuuint64_t)cols, (cuuint64_t)rows};
  cuuint64_t strides[1] = {(cuuint64_t)cols * 2};
  cuuint32_t box[2] = {64, (cuuint32_t)box_rows};
  cuuint32_t es[2] = {1, 1};
  enc(tm, CU_TENSOR_MAP_DATA_TYPE_BFLOAT16, 2, const_cast<void*>(ptr), dims, strides, box, es, CU_TENSOR_MAP_INTERLEAVE_NONE,
      CU_TENSOR_MAP_SWIZZLE_128B, CU_TENSOR_MAP_L2_PROMOTION_L2_256B, CU_TENSOR_MAP_FLOAT_OOB_FILL_NONE);
}

}

extern "C" void kernel_launch(void* const* d_in, const int* in_sizes, int n_in, void* d_out, int out_size) {
  (void)in_sizes; (void)n_in; (void)out_size;
  static EncodeFn enc = nullptr;
  if (!enc) {
    void* fn = nullptr;
    cudaDriverEntryPointQueryResult qr;
    cudaGetDriverEntryPoint("cuTensorMapEncodeTiled", &fn, cudaEnableDefault, &qr);
    enc = (EncodeFn)fn;
    cudaFuncSetAttribute(mega_kernel, cudaFuncAttributeMaxDynamicSharedMemorySize, SMEM_BYTES);
  }
  Params P;
  make_map(enc, &P.tm_ckv, d_in[1], 512, 2048, 64);
  make_map(enc, &P.tm_wq, d_in[2], 4096, 512, 128);
  make_map(enc, &P.tm_wuk, d_in[3], 4096, 512, 128);
  make_map(enc, &P.tm_wuv, d_in[4], 4096, 512, 128);
  make_map(enc, &P.tm_wo, d_in[5], 512, 4096, 64);
  P.x = (const __nv_bfloat16*)d_in[0];
  P.w_q = (const __nv_bfloat16*)d_in[2];
  P.w_uk = (const __nv_bfloat16*)d_in[3];
  P.w_uv = (const __nv_bfloat16*)d_in[4];
  P.w_o = (const __nv_bfloat16*)d_in[5];
  P.w_r = (const __nv_bfloat16*)d_in[7];
  P.w_gate = (const __nv_bfloat16*)d_in[8];
  P.w_up = (const __nv_bfloat16*)d_in[9];
  P.w_down = (const __nv_bfloat16*)d_in[10];
  P.out = (__nv_bfloat16*)d_out;
  P.zero = 0;
  cudaLaunchConfig_t cfg = {};
  cfg.gridDim = dim3(NCTA); cfg.blockDim = dim3(384); cfg.dynamicSmemBytes = SMEM_BYTES; cfg.stream = cudaStreamPerThread;
  cudaLaunchAttribute at[1];
  at[0].id = cudaLaunchAttributeClusterDimension; at[0].val.clusterDim.x = 2; at[0].val.clusterDim.y = 1; at[0].val.clusterDim.z = 1;
  cfg.attrs = at; cfg.numAttrs = 1;
  cudaLaunchKernelEx(&cfg, mega_kernel, P);
}
```

```cpp
#include <cuda_runtime.h>
#include <cuda_bf16.h>
#include <cuda.h>
#include <stdint.h>
#include <limits.h>
#include <type_traits>

namespace {

#define PF_NS 1500
#define PF_PER 4100
#define PP1 9
#define PF_T 3
#define NK 2
#define NQ 5
#define PF_B 1400
constexpr int DM = 512, NH = 32, FF = 1792;
constexpr int NCTA = 132;
constexpr int NST = 6;
constexpr uint32_t STAGE = 32768;
constexpr uint32_t SM_STG = NST * STAGE;
constexpr uint32_t SM_BAR = SM_STG + 32768;
constexpr uint32_t SM_WR = SM_BAR + 256;
constexpr uint32_t SMEM_BYTES = SM_WR + 1024 + 1024;
constexpr float QSCALE = 0.08838834764831845f * 1.4426950408889634f;
constexpr uint32_t B_FULL = 0, B_EMPTY = 64, B_STFREE = 128, B_DONE = 144, B_EPOCH = 160;

struct alignas(64) Params {
  CUtensorMap tm_x, tm_ckv, tm_wq, tm_wuk, tm_wuv, tm_wo, tm_wg, tm_wu;
  const __nv_bfloat16 *x, *ckv, *w_q, *w_uk, *w_uv, *w_o, *w_r, *w_down;
  __nv_bfloat16* out;
  uint32_t zero;
};

struct Flags {
  unsigned long long key[2]; unsigned pad0[28];
  unsigned exit_cnt; unsigned pad1[31];
  unsigned ln_done; unsigned pad2[31];
  unsigned moe_done; unsigned pad3[31];
  unsigned moe_fin; unsigned pad4[31];
  unsigned kv_done[32];
  unsigned q_done[32];
  unsigned ctx[256][8];
};

__device__ Flags g_flags;
__device__ __align__(1024) unsigned char g_kv[(size_t)NH * 2 * 16 * 32768];
__device__ __align__(1024) uint2 g_stat[2048];
__device__ __align__(1024) unsigned char g_qc[(size_t)32 * NH * 16384];
__device__ __align__(1024) uint4 g_exch[(size_t)16 * 4 * 3 * 4 * 512];
__device__ float g_ypart[4 * DM];
__device__ __align__(16) uint32_t g_selrow[DM / 2];

__device__ __forceinline__ uint32_t smem_u32(const void* p) { return (uint32_t)__cvta_generic_to_shared(p); }
__device__ __forceinline__ void mbar_init(uint32_t bar, int cnt) {
  asm volatile("mbarrier.init.shared::cta.b64 [%0], %1;" ::"r"(bar), "r"(cnt) : "memory");
}
__device__ __forceinline__ void mbar_expect_tx(uint32_t bar, uint32_t bytes) {
  asm volatile("mbarrier.arrive.expect_tx.shared::cta.b64 _, [%0], %1;" ::"r"(bar), "r"(bytes) : "memory");
}
__device__ __forceinline__ void mbar_arrive(uint32_t bar) {
  asm volatile("mbarrier.arrive.shared::cta.b64 _, [%0];" ::"r"(bar) : "memory");
}
__device__ __forceinline__ uint32_t mapa(uint32_t addr, uint32_t cta) {
  uint32_t r; asm volatile("mapa.shared::cluster.u32 %0, %1, %2;" : "=r"(r) : "r"(addr), "r"(cta)); return r;
}
__device__ __forceinline__ void mbar_arrive_cluster(uint32_t bar, uint32_t cnt) {
  asm volatile("mbarrier.arrive.shared::cluster.b64 _, [%0], %1;" ::"r"(bar), "r"(cnt) : "memory");
}
__device__ __forceinline__ uint32_t mbar_test2(uint32_t b0, uint32_t p0, uint32_t b1, uint32_t p1) {
  uint32_t ok;
  asm volatile("{\n.reg .pred p, q;\nmbarrier.test_wait.parity.shared::cta.b64 p, [%1], %2;\nmbarrier.test_wait.parity.shared::cta.b64 q, [%3], %4;\n"
               "and.pred p, p, q;\nselp.u32 %0, 1, 0, p;\n}\n" : "=r"(ok) : "r"(b0), "r"(p0), "r"(b1), "r"(p1) : "memory");
  return ok;
}
__device__ __forceinline__ bool mbar_try(uint32_t bar, uint32_t parity) {
  uint32_t ok;
  asm volatile("{\n.reg .pred p;\nmbarrier.try_wait.parity.shared::cta.b64 p, [%1], %2, %3;\nselp.u32 %0, 1, 0, p;\n}\n"
               : "=r"(ok) : "r"(bar), "r"(parity), "r"(4000) : "memory");
  return ok != 0;
}
__device__ __forceinline__ bool elect_one() {
  uint32_t p;
  asm volatile("{\n.reg .pred p;\nelect.sync _|p, 0xffffffff;\nselp.u32 %0, 1, 0, p;\n}\n" : "=r"(p));
  return p != 0;
}
__device__ __forceinline__ uint32_t clk32() { uint32_t c; asm volatile("mov.u32 %0, %%clock;" : "=r"(c)); return c; }
constexpr uint32_t TIMEOUT_CLKS = 1u << 30;
__device__ __forceinline__ void mbar_wait(uint32_t bar, uint32_t parity) {
  asm volatile("{\n.reg .pred p;\nWAIT_LOOP:\nmbarrier.try_wait.parity.shared::cta.b64 p, [%0], %1;\n@p bra WAIT_DONE;\nbra WAIT_LOOP;\nWAIT_DONE:\n}\n"
               ::"r"(bar), "r"(parity) : "memory");
}
#define TH 4000
__device__ __forceinline__ void mbar_park(uint32_t bar, uint32_t parity) {
  asm volatile("{\n.reg .pred p;\nWAIT_LOOP:\nmbarrier.try_wait.parity.shared::cta.b64 p, [%0], %1, %2;\n@p bra WAIT_DONE;\nbra WAIT_LOOP;\nWAIT_DONE:\n}\n"
               ::"r"(bar), "r"(parity), "r"(TH) : "memory");
}
__device__ __forceinline__ unsigned ld_acquire(const unsigned* p) {
  unsigned v; asm volatile("ld.acquire.gpu.global.u32 %0, [%1];" : "=r"(v) : "l"(p) : "memory"); return v;
}
__device__ __forceinline__ void red_release(unsigned* p, unsigned v) {
  asm volatile("red.release.gpu.global.add.u32 [%0], %1;" ::"l"(p), "r"(v) : "memory");
}
__device__ __forceinline__ void red_relaxed(unsigned* p, unsigned v) {
  asm volatile("red.relaxed.gpu.global.add.u32 [%0], %1;" ::"l"(p), "r"(v) : "memory");
}
__device__ __forceinline__ void st_relaxed128(uint4* p, uint32_t a, uint32_t b, uint32_t c, uint32_t d) {
  asm volatile("{\n.reg .b128 v;\nmov.b128 v, {%1,%2,%3,%4};\nst.relaxed.gpu.global.b128 [%0], v;\n}\n" ::"l"(p), "r"(a), "r"(b), "r"(c), "r"(d) : "memory");
}
__device__ __forceinline__ uint4 ld_relaxed128(const uint4* p) {
  uint4 v;
  asm volatile("{\n.reg .b128 v;\nld.relaxed.gpu.global.b128 v, [%4];\nmov.b128 {%0,%1,%2,%3}, v;\n}\n"
               : "=r"(v.x), "=r"(v.y), "=r"(v.z), "=r"(v.w) : "l"(p) : "memory");
  return v;
}
__device__ __forceinline__ unsigned ld_relaxed(const unsigned* p) {
  unsigned v; asm volatile("ld.relaxed.gpu.global.u32 %0, [%1];" : "=r"(v) : "l"(p) : "memory"); return v;
}
__device__ __forceinline__ bool flag_ok(const unsigned* p, unsigned target) { return (int)(ld_acquire(p) - target) >= 0; }
__device__ __forceinline__ void flag_wait(const unsigned* p, unsigned target) {
  while (!flag_ok(p, target)) { __nanosleep(40); }
}
__device__ __forceinline__ void fence_gpu() { asm volatile("fence.acq_rel.gpu;" ::: "memory"); }
__device__ __forceinline__ void fence_async_global() { asm volatile("fence.proxy.async.global;" ::: "memory"); }
__device__ __forceinline__ void fence_async_smem() { asm volatile("fence.proxy.async.shared::cta;" ::: "memory"); }
__device__ __forceinline__ void bar_sync(int id, int n) { asm volatile("bar.sync %0, %1;" ::"r"(id), "r"(n) : "memory"); }
__device__ __forceinline__ void bar_arrive(int id, int n) { asm volatile("bar.arrive %0, %1;" ::"r"(id), "r"(n) : "memory"); }

constexpr uint64_t EV_NORMAL = 0x1000000000000000ull, EV_FIRST = 0x12F0000000000000ull;
#define HINTS 60
constexpr uint64_t H_W = (HINTS & 1) ? EV_FIRST : EV_NORMAL, H_A = (HINTS & 2) ? EV_FIRST : EV_NORMAL, H_KV = (HINTS & 4) ? EV_FIRST : EV_NORMAL,
                   H_Q = (HINTS & 8) ? EV_FIRST : EV_NORMAL, H_OP = (HINTS & 16) ? EV_FIRST : EV_NORMAL, H_S1 = (HINTS & 32) ? EV_FIRST : EV_NORMAL,
                   H_PF = (HINTS & 64) ? EV_FIRST : EV_NORMAL;
__device__ __forceinline__ void bulk_load(uint32_t dst, const void* src, uint32_t bytes, uint32_t bar, uint64_t pol) {
  asm volatile("cp.async.bulk.shared::cluster.global.mbarrier::complete_tx::bytes.L2::cache_hint [%0], [%1], %2, [%3], %4;"
               ::"r"(dst), "l"(src), "r"(bytes), "r"(bar), "l"(pol) : "memory");
}
__device__ __forceinline__ void bulk_load_mc(uint32_t dst, const void* src, uint32_t bytes, uint32_t bar, uint64_t pol) {
  asm volatile("cp.async.bulk.shared::cluster.global.mbarrier::complete_tx::bytes.multicast::cluster.L2::cache_hint [%0], [%1], %2, [%3], %4, %5;"
               ::"r"(dst), "l"(src), "r"(bytes), "r"(bar), "h"((uint16_t)3), "l"(pol) : "memory");
}
__device__ __forceinline__ void tma_load(uint32_t dst, const CUtensorMap* tm, int c0, int c1, uint32_t bar, uint64_t pol) {
  asm volatile("cp.async.bulk.tensor.2d.shared::cluster.global.mbarrier::complete_tx::bytes.L2::cache_hint [%0], [%1, {%3, %4}], [%2], %5;"
               ::"r"(dst), "l"(tm), "r"(bar), "r"(c0), "r"(c1), "l"(pol) : "memory");
}
__device__ __forceinline__ void tma_load_mc(uint32_t dst, const CUtensorMap* tm, int c0, int c1, uint32_t bar, uint64_t pol) {
  asm volatile("cp.async.bulk.tensor.2d.shared::cluster.global.mbarrier::complete_tx::bytes.multicast::cluster.L2::cache_hint [%0], [%1, {%3, %4}], [%2], %5, %6;"
               ::"r"(dst), "l"(tm), "r"(bar), "r"(c0), "r"(c1), "h"((uint16_t)3), "l"(pol) : "memory");
}
__device__ __forceinline__ void bulk_store(void* dst, uint32_t src, uint32_t bytes, uint64_t pol) {
  asm volatile("cp.async.bulk.global.shared::cta.bulk_group.L2::cache_hint [%0], [%1], %2, %3;" ::"l"(dst), "r"(src), "r"(bytes), "l"(pol) : "memory");
}
__device__ __forceinline__ void bulk_commit() { asm volatile("cp.async.bulk.commit_group;" ::: "memory"); }
__device__ __forceinline__ void bulk_wait_read0() { asm volatile("cp.async.bulk.wait_group.read 0;" ::: "memory"); }
__device__ __forceinline__ void bulk_wait0() { asm volatile("cp.async.bulk.wait_group 0;" ::: "memory"); }
__device__ __forceinline__ void l2_prefetch(const void* p, uint32_t bytes, uint64_t pol = EV_NORMAL) {
  asm volatile("cp.async.bulk.prefetch.L2.global.L2::cache_hint [%0], %1, %2;" ::"l"(p), "r"(bytes), "l"(pol) : "memory");
}

__device__ __forceinline__ void touch256(const void* p) {
  asm volatile("{\n.reg .b32 t;\nld.global.nc.L1::no_allocate.L2::256B.b32 t, [%0];\n}" ::"l"(p) : "memory");
}

#define WG_FENCE() asm volatile("wgmma.fence.sync.aligned;" ::: "memory")
#define WG_COMMIT() asm volatile("wgmma.commit_group.sync.aligned;" ::: "memory")
#define WG_WAIT(n) asm volatile("wgmma.wait_group.sync.aligned %0;" ::"n"(n) : "memory")

#define R8(a, o) "+f"(a[o + 0]), "+f"(a[o + 1]), "+f"(a[o + 2]), "+f"(a[o + 3]), "+f"(a[o + 4]), "+f"(a[o + 5]), "+f"(a[o + 6]), "+f"(a[o + 7])
#define R32(a, o) R8(a, o), R8(a, o + 8), R8(a, o + 16), R8(a, o + 24)
#define R64(a, o) R32(a, o), R32(a, o + 32)
#define ACC64 "{%0,%1,%2,%3,%4,%5,%6,%7,%8,%9,%10,%11,%12,%13,%14,%15,%16,%17,%18,%19,%20,%21,%22,%23,%24,%25,%26,%27,%28,%29,%30,%31," \
              "%32,%33,%34,%35,%36,%37,%38,%39,%40,%41,%42,%43,%44,%45,%46,%47,%48,%49,%50,%51,%52,%53,%54,%55,%56,%57,%58,%59,%60,%61,%62,%63}"

constexpr uint32_t DESC_HI = (1024u >> 4) | (1u << 30);
__device__ __forceinline__ uint32_t desc_lo(uint32_t addr, uint32_t lbo) { return ((addr & 0x3FFFFu) >> 4) | ((lbo >> 4) << 16); }

template <int TB>
__device__ __forceinline__ void mma_rs128(float (&d)[64], uint32_t a0, uint32_t a1, uint32_t a2, uint32_t a3, uint32_t blo, int acc) {
  asm volatile("{\n.reg .pred p;\n.reg .b64 db;\nsetp.ne.b32 p, %69, 0;\nmov.b64 db, {%68, %71};\n"
               "wgmma.mma_async.sync.aligned.m64n128k16.f32.bf16.bf16 " ACC64 ", {%64,%65,%66,%67}, db, p, 1, 1, %70;\n}\n"
               : R64(d, 0) : "r"(a0), "r"(a1), "r"(a2), "r"(a3), "r"(blo), "r"(acc), "n"(TB), "r"(DESC_HI));
}
#define ACC32 "{%0,%1,%2,%3,%4,%5,%6,%7,%8,%9,%10,%11,%12,%13,%14,%15,%16,%17,%18,%19,%20,%21,%22,%23,%24,%25,%26,%27,%28,%29,%30,%31}"
#define W8(a, o) "=f"(a[o + 0]), "=f"(a[o + 1]), "=f"(a[o + 2]), "=f"(a[o + 3]), "=f"(a[o + 4]), "=f"(a[o + 5]), "=f"(a[o + 6]), "=f"(a[o + 7])
#define W32(a, o) W8(a, o), W8(a, o + 8), W8(a, o + 16), W8(a, o + 24)
#define W64(a, o) W32(a, o), W32(a, o + 32)
#define QK_RS64 "{\n.reg .pred p;\n.reg .b64 db;\nsetp.ne.b32 p, %37, 0;\nmov.b64 db, {%36, %38};\n" \
                "wgmma.mma_async.sync.aligned.m64n64k16.f32.bf16.bf16 " ACC32 ", {%32,%33,%34,%35}, db, p, 1, 1, 0;\n}\n"
#define QK_SS64 "{\n.reg .pred p;\n.reg .b64 da, db;\nsetp.ne.b32 p, %34, 0;\nmov.b64 da, {%32, %35};\nmov.b64 db, {%33, %35};\n" \
                "wgmma.mma_async.sync.aligned.m64n64k16.f32.bf16.bf16 " ACC32 ", da, db, p, 1, 1, 0, 0;\n}\n"
#define QK_RS128 "{\n.reg .pred p;\n.reg .b64 db;\nsetp.ne.b32 p, %69, 0;\nmov.b64 db, {%68, %70};\n" \
                 "wgmma.mma_async.sync.aligned.m64n128k16.f32.bf16.bf16 " ACC64 ", {%64,%65,%66,%67}, db, p, 1, 1, 0;\n}\n"
#define QK_SS128 "{\n.reg .pred p;\n.reg .b64 da, db;\nsetp.ne.b32 p, %66, 0;\nmov.b64 da, {%64, %67};\nmov.b64 db, {%65, %67};\n" \
                 "wgmma.mma_async.sync.aligned.m64n128k16.f32.bf16.bf16 " ACC64 ", da, db, p, 1, 1, 0, 0;\n}\n"
__device__ __forceinline__ void qk_rs(float (&d)[32], const uint32_t* a, uint32_t blo, bool) {
  asm volatile(QK_RS64 : R32(d, 0) : "r"(a[0]), "r"(a[1]), "r"(a[2]), "r"(a[3]), "r"(blo), "n"(1), "r"(DESC_HI));
}
__device__ __forceinline__ void qk_rs(float (&d)[64], const uint32_t* a, uint32_t blo, bool acc) {
  if (acc) asm volatile(QK_RS128 : R64(d, 0) : "r"(a[0]), "r"(a[1]), "r"(a[2]), "r"(a[3]), "r"(blo), "n"(1), "r"(DESC_HI));
  else asm volatile(QK_RS128 : W64(d, 0) : "r"(a[0]), "r"(a[1]), "r"(a[2]), "r"(a[3]), "r"(blo), "n"(0), "r"(DESC_HI));
}
__device__ __forceinline__ void qk_ss(float (&d)[32], uint32_t alo, uint32_t blo, bool) {
  asm volatile(QK_SS64 : R32(d, 0) : "r"(alo), "r"(blo), "n"(1), "r"(DESC_HI));
}
__device__ __forceinline__ void qk_ss(float (&d)[64], uint32_t alo, uint32_t blo, bool acc) {
  if (acc) asm volatile(QK_SS128 : R64(d, 0) : "r"(alo), "r"(blo), "n"(1), "r"(DESC_HI));
  else asm volatile(QK_SS128 : W64(d, 0) : "r"(alo), "r"(blo), "n"(0), "r"(DESC_HI));
}
__device__ __forceinline__ void mma_ss256(float (&d)[128], uint32_t alo, uint32_t blo, int acc) {
  asm volatile("{\n.reg .pred p;\n.reg .b64 da, db;\nsetp.ne.b32 p, %130, 0;\nmov.b64 da, {%128, %131};\nmov.b64 db, {%129, %131};\n"
               "wgmma.mma_async.sync.aligned.m64n256k16.f32.bf16.bf16 "
               "{%0,%1,%2,%3,%4,%5,%6,%7,%8,%9,%10,%11,%12,%13,%14,%15,%16,%17,%18,%19,%20,%21,%22,%23,%24,%25,%26,%27,%28,%29,%30,%31,"
               "%32,%33,%34,%35,%36,%37,%38,%39,%40,%41,%42,%43,%44,%45,%46,%47,%48,%49,%50,%51,%52,%53,%54,%55,%56,%57,%58,%59,%60,%61,%62,%63,"
               "%64,%65,%66,%67,%68,%69,%70,%71,%72,%73,%74,%75,%76,%77,%78,%79,%80,%81,%82,%83,%84,%85,%86,%87,%88,%89,%90,%91,%92,%93,%94,%95,"
               "%96,%97,%98,%99,%100,%101,%102,%103,%104,%105,%106,%107,%108,%109,%110,%111,%112,%113,%114,%115,%116,%117,%118,%119,%120,%121,%122,%123,%124,%125,%126,%127},"
               " da, db, p, 1, 1, 0, 1;\n}\n"
               : R64(d, 0), R64(d, 64) : "r"(alo), "r"(blo), "r"(acc), "r"(DESC_HI));
}
__device__ __forceinline__ void mma_ss192(float (&d)[128], uint32_t alo, uint32_t blo) {
  asm volatile("{\n.reg .pred p;\n.reg .b64 da, db;\nsetp.ne.b32 p, %98, 0;\nmov.b64 da, {%96, %99};\nmov.b64 db, {%97, %99};\n"
               "wgmma.mma_async.sync.aligned.m64n192k16.f32.bf16.bf16 "
               "{%0,%1,%2,%3,%4,%5,%6,%7,%8,%9,%10,%11,%12,%13,%14,%15,%16,%17,%18,%19,%20,%21,%22,%23,%24,%25,%26,%27,%28,%29,%30,%31,"
               "%32,%33,%34,%35,%36,%37,%38,%39,%40,%41,%42,%43,%44,%45,%46,%47,%48,%49,%50,%51,%52,%53,%54,%55,%56,%57,%58,%59,%60,%61,%62,%63,"
               "%64,%65,%66,%67,%68,%69,%70,%71,%72,%73,%74,%75,%76,%77,%78,%79,%80,%81,%82,%83,%84,%85,%86,%87,%88,%89,%90,%91,%92,%93,%94,%95},"
               " da, db, p, 1, 1, 0, 1;\n}\n"
               : R64(d, 0), R32(d, 64) : "r"(alo), "r"(blo), "n"(1), "r"(DESC_HI));
}
#define OP_SS64 "{\n.reg .pred p;\n.reg .b64 da, db;\nsetp.ne.b32 p, %34, 0;\nmov.b64 da, {%32, %35};\nmov.b64 db, {%33, %35};\n" \
                "wgmma.mma_async.sync.aligned.m64n64k16.f32.bf16.bf16 " ACC32 ", da, db, p, 1, 1, 0, 1;\n}\n"
__device__ __forceinline__ void mma_ss64(float (&d)[32], uint32_t alo, uint32_t blo, bool acc) {
  if (acc) asm volatile(OP_SS64 : R32(d, 0) : "r"(alo), "r"(blo), "n"(1), "r"(DESC_HI));
  else asm volatile(OP_SS64 : W32(d, 0) : "r"(alo), "r"(blo), "n"(0), "r"(DESC_HI));
}
template <int N>
__device__ __forceinline__ void fence_regs(float (&d)[N]) {
#pragma unroll
  for (int i = 0; i < N; i++) asm volatile("" : "+f"(d[i])::"memory");
}
__device__ __forceinline__ uint32_t pack_bf16(float lo, float hi) {
  uint32_t r; asm("cvt.rn.bf16x2.f32 %0, %1, %2;" : "=r"(r) : "f"(hi), "f"(lo)); return r;
}
__device__ __forceinline__ uint32_t add_bf16x2(uint32_t a, uint32_t b) {
  uint32_t r; asm("add.rn.bf16x2 %0, %1, %2;" : "=r"(r) : "r"(a), "r"(b)); return r;
}
__device__ __forceinline__ uint32_t mul_bf16x2(uint32_t a, uint32_t b) {
  uint32_t r; asm("mul.rn.bf16x2 %0, %1, %2;" : "=r"(r) : "r"(a), "r"(b)); return r;
}
__device__ __forceinline__ uint32_t fma_bf16x2(uint32_t a, uint32_t b, uint32_t c) {
  uint32_t r; asm("fma.rn.bf16x2 %0, %1, %2, %3;" : "=r"(r) : "r"(a), "r"(b), "r"(c)); return r;
}
__device__ __forceinline__ float bf16_round(float v) { return __bfloat162float(__float2bfloat16_rn(v)); }
__device__ __forceinline__ float bf_lo(uint32_t v) { return __uint_as_float(v << 16); }
__device__ __forceinline__ float bf_hi(uint32_t v) { return __uint_as_float(v & 0xFFFF0000u); }
__device__ __forceinline__ float ex2v(float x) { float y; asm volatile("ex2.approx.ftz.f32 %0, %1;" : "=f"(y) : "f"(x)); return y; }
__device__ __forceinline__ float rcp(float x) { float y; asm("rcp.approx.ftz.f32 %0, %1;" : "=f"(y) : "f"(x)); return y; }
__device__ __forceinline__ float add_sat(float a, float b) { float y; asm("add.sat.f32 %0, %1, %2;" : "=f"(y) : "f"(a), "f"(b)); return y; }
__device__ __forceinline__ float ex2(float x) { float y; asm("ex2.approx.ftz.f32 %0, %1;" : "=f"(y) : "f"(x)); return y; }
__device__ __forceinline__ void stmatrix4(uint32_t addr, uint32_t r0, uint32_t r1, uint32_t r2, uint32_t r3) {
  asm volatile("stmatrix.sync.aligned.m8n8.x4.shared.b16 [%0], {%1,%2,%3,%4};" ::"r"(addr), "r"(r0), "r"(r1), "r"(r2), "r"(r3) : "memory");
}
__device__ __forceinline__ void ldmatrix4(uint32_t addr, uint32_t& r0, uint32_t& r1, uint32_t& r2, uint32_t& r3) {
  asm volatile("ldmatrix.sync.aligned.m8n8.x4.shared.b16 {%0,%1,%2,%3}, [%4];" : "=r"(r0), "=r"(r1), "=r"(r2), "=r"(r3) : "r"(addr) : "memory");
}
__device__ __forceinline__ void stmatrix4_t(uint32_t addr, uint32_t r0, uint32_t r1, uint32_t r2, uint32_t r3) {
  asm volatile("stmatrix.sync.aligned.m8n8.x4.trans.shared.b16 [%0], {%1,%2,%3,%4};" ::"r"(addr), "r"(r0), "r"(r1), "r"(r2), "r"(r3) : "memory");
}
__device__ __forceinline__ void ldmatrix4_t(uint32_t addr, uint32_t& r0, uint32_t& r1, uint32_t& r2, uint32_t& r3) {
  asm volatile("ldmatrix.sync.aligned.m8n8.x4.trans.shared.b16 {%0,%1,%2,%3}, [%4];" : "=r"(r0), "=r"(r1), "=r"(r2), "=r"(r3) : "r"(addr) : "memory");
}
__device__ __forceinline__ void mma_16816(float* c, const uint32_t* a, uint32_t b0, uint32_t b1) {
  asm volatile("mma.sync.aligned.m16n8k16.row.col.f32.bf16.bf16.f32 {%0,%1,%2,%3}, {%4,%5,%6,%7}, {%8,%9}, {%0,%1,%2,%3};"
               : "+f"(c[0]), "+f"(c[1]), "+f"(c[2]), "+f"(c[3]) : "r"(a[0]), "r"(a[1]), "r"(a[2]), "r"(a[3]), "r"(b0), "r"(b1));
}
__device__ __forceinline__ void cluster_arrive() { asm volatile("barrier.cluster.arrive.relaxed;" ::: "memory"); }
__device__ __forceinline__ void cluster_wait() { asm volatile("barrier.cluster.wait;" ::: "memory"); }

__device__ __forceinline__ uint32_t read_epoch() {
  uint32_t v; asm volatile("ld.relaxed.gpu.global.u32 %0, [%1];" : "=r"(v) : "l"(&g_flags.exit_cnt) : "memory");
  return v / NCTA;
}
__device__ __forceinline__ uint32_t lds32(uint32_t a) { uint32_t v; asm volatile("ld.shared.u32 %0, [%1];" : "=r"(v) : "r"(a) : "memory"); return v; }
__device__ __forceinline__ uint32_t rnext(uint32_t r) { r += 8; return r >= NST * 8 ? (r - NST * 8) ^ 1u : r; }

#define PROF(role, slot) do { } while (0)
#define PROFC(slot) do { } while (0)
#define PROFP(slot) do { } while (0)

struct Cons {
  uint32_t sb;
  uint32_t bars;
  int w;
  int warp;
  int lane;
  uint32_t rank;
  uint32_t ring;
  uint32_t stphase;
  uint32_t epoch;
  uint32_t ebase;
  uint32_t zero;
  __device__ __forceinline__ void wait_full(uint32_t r) { mbar_wait(bars + B_FULL + (r & ~7u), r & 1u); }
  __device__ __forceinline__ uint32_t stage_addr(uint32_t r) { return sb + ((r & ~7u) << 12); }
  __device__ __forceinline__ void release(uint32_t r, uint32_t n = 1) { if (ebase) mbar_arrive_cluster(ebase + (r & ~7u), n); }
  template <int N>
  __device__ __forceinline__ void release_after(const uint32_t* regs, uint32_t r, uint32_t n = 1) {
    uint32_t d = 0;
#pragma unroll
    for (int i = 0; i < N; i++) d ^= regs[4 * i];
    __syncwarp();
    if (ebase) mbar_arrive_cluster(ebase + (r & ~7u) + (d & zero), n);
  }
  __device__ __forceinline__ void turn_sync() { bar_sync(1 + w, 256); }
  __device__ __forceinline__ void turn_pass() { bar_arrive(2 - w, 256); }
  __device__ __forceinline__ uint32_t frag_off() {
    const int mat = lane >> 3;
    return (warp * 16 + (mat & 1) * 8 + (lane & 7)) * 128 + ((((mat >> 1) ^ lane) & 7) << 4);
  }
  __device__ __forceinline__ void stage_out(const float (&a)[64], float s0, float s1) { stage_write(a, s0, s1); stage_send(); }
  __device__ __forceinline__ void stage_send() { fence_async_smem(); bar_arrive(3 + w, 160); }
  __device__ __forceinline__ void stage_write(const float (&a)[64], float s0, float s1) {
    mbar_wait(bars + B_STFREE + w * 8, stphase); stphase ^= 1;
    const uint32_t base = sb + SM_STG + w * 16384 + frag_off();
#pragma unroll
    for (int jj = 0; jj < 8; jj++) {
      const uint32_t r0 = pack_bf16(a[8 * jj + 0] * s0, a[8 * jj + 1] * s0), r1 = pack_bf16(a[8 * jj + 2] * s1, a[8 * jj + 3] * s1);
      const uint32_t r2 = pack_bf16(a[8 * jj + 4] * s0, a[8 * jj + 5] * s0), r3 = pack_bf16(a[8 * jj + 6] * s1, a[8 * jj + 7] * s1);
      stmatrix4((base ^ (((2 * jj) & 7) << 4)) + (jj >> 2) * 8192, r0, r1, r2, r3);
    }
  }
};

__device__ __forceinline__ int proj_tiles(int cg) { return cg < 5 ? 12 : (cg < 7 ? 11 : 10); }
__device__ __forceinline__ void proj_phase(Cons& C, const Params& P, const int cg, const int g) {
  uint32_t af[128];
  float acc[64];
  float s0 = 1.f, s1 = 1.f, e0 = 0.f, e1 = 0.f;
  if (cg == 7 && C.w == 0 && C.warp < 2) {
    const uint4 v = __ldg(reinterpret_cast<const uint4*>(P.w_r) + C.warp * 32 + C.lane);
    asm volatile("st.shared.v4.u32 [%0], {%1,%2,%3,%4};" ::"r"(C.sb + SM_WR + (C.warp * 32 + C.lane) * 16), "r"(v.x), "r"(v.y), "r"(v.z), "r"(v.w) : "memory");
  }
  {
    const bool isq = cg >= 5;
    const int nt = proj_tiles(cg);
    auto fetch = [&](int c) {
      C.wait_full(C.ring);
      const uint32_t base = C.stage_addr(C.ring) + C.w * 16384 + C.frag_off();
#pragma unroll
      for (int kk = 0; kk < 8; kk++)
        ldmatrix4((base ^ ((2 * (kk & 3)) << 4)) + (kk >> 2) * 8192, af[c * 32 + kk * 4], af[c * 32 + kk * 4 + 1], af[c * 32 + kk * 4 + 2],
                  af[c * 32 + kk * 4 + 3]);
      C.release_after<8>(af + c * 32, C.ring);
      C.ring = rnext(C.ring);
    };
    auto product = [&](int c, uint32_t& prev) {
      C.wait_full(C.ring);
      const uint32_t blo = desc_lo(C.stage_addr(C.ring), 16384);
      WG_FENCE();
#pragma unroll
      for (int kk = 0; kk < 8; kk++)
        mma_rs128<1>(acc, af[c * 32 + kk * 4], af[c * 32 + kk * 4 + 1], af[c * 32 + kk * 4 + 2], af[c * 32 + kk * 4 + 3], blo + kk * 128,
                     (c | kk) != 0);
      WG_COMMIT();
    };
    uint32_t n0 = 0, n1 = 0;
    if (isq) {
      float c[16];
#pragma unroll
      for (int i = 0; i < 16; i++) c[i] = 0.f;
#pragma unroll
      for (int ch = 0; ch < 4; ch++) {
        fetch(ch);
#pragma unroll
        for (int kk = 8 * ch; kk < 8 * ch + 8; kk++) mma_16816(c + 4 * (kk & 3), af + 4 * kk, 0x3F803F80u, 0x3F803F80u);
      }
      PROFC(55);
      const float mean0 = ((c[0] + c[4]) + (c[8] + c[12])) * (1.0f / DM), mean1 = ((c[2] + c[6]) + (c[10] + c[14])) * (1.0f / DM);
      n0 = pack_bf16(-mean0, -mean0); n1 = pack_bf16(-mean1, -mean1);
      e0 = mean0 + bf_lo(n0); e1 = mean1 + bf_lo(n1);
#pragma unroll
      for (int i = 0; i < 128; i++) af[i] = add_bf16x2(af[i], (i & 1) ? n1 : n0);
      PROFC(56);
    }
    uint32_t prev = 0;
    {
      float v[4] = {0.f, 0.f, 0.f, 0.f};
#pragma unroll
      for (int c = 0; c < 4; c++) {
        if (!isq) fetch(c);
        if (!isq && c == 0) PROFC(55);
        if (!isq && c == 3) PROFC(56);
        C.turn_sync();
        product(c, prev);
        C.turn_pass();
        if (isq) {
#pragma unroll
          for (int i = 32 * c; i < 32 * c + 32; i++) {
            v[i & 1] = fmaf(bf_lo(af[i]), bf_lo(af[i]), v[i & 1]);
            v[2 + (i & 1)] = fmaf(bf_hi(af[i]), bf_hi(af[i]), v[2 + (i & 1)]);
          }
        }
        if (c > 0) { WG_WAIT(1); C.release(prev); }
        prev = C.ring;
        C.ring = rnext(C.ring);
      }
      if (isq) {
        float v0 = v[0] + v[2], v1 = v[1] + v[3];
        v0 += __shfl_xor_sync(0xffffffffu, v0, 1); v1 += __shfl_xor_sync(0xffffffffu, v1, 1);
        v0 += __shfl_xor_sync(0xffffffffu, v0, 2); v1 += __shfl_xor_sync(0xffffffffu, v1, 2);
        v0 = bf16_round(fmaxf(v0 * (1.0f / DM) - e0 * e0, 0.f)); v1 = bf16_round(fmaxf(v1 * (1.0f / DM) - e1 * e1, 0.f));
        e0 = __fdividef(1.0f, bf16_round(sqrtf(bf16_round(v0 + 1e-5f)))); e1 = __fdividef(1.0f, bf16_round(sqrtf(bf16_round(v1 + 1e-5f))));
        s0 = e0 * QSCALE; s1 = e1 * QSCALE;
        if (cg == 7 && (C.lane & 3) == 0) {
          const int row = g * 64 + C.warp * 16 + (C.lane >> 2);
          g_stat[row] = make_uint2(n0, __float_as_uint(e0)); g_stat[row + 8] = make_uint2(n1, __float_as_uint(e1));
        }
      }
    }
#pragma unroll 1
    for (int t = 0; t < nt; t++) {
      if (t > 0) {
        C.turn_sync();
#pragma unroll
        for (int c = 0; c < 4; c++) {
          product(c, prev);
          if (c == 3) C.turn_pass();
          if (c > 0) { WG_WAIT(1); C.release(prev); }
          prev = C.ring;
          C.ring = rnext(C.ring);
        }
      }
      WG_WAIT(0);
      C.release(prev);
      fence_regs(acc);
      C.stage_out(acc, s0, s1);
      PROFC(t + 12 - nt);
      if (t == 1) C.epoch = lds32(C.bars + B_EPOCH + C.w * 4);
      if (cg == 7 && t == 1) {
        const uint32_t h0 = pack_bf16(e0, e0), h1 = pack_bf16(e1, e1);
        const uint32_t l0 = pack_bf16(e0 - bf_lo(h0), e0 - bf_lo(h0)), l1 = pack_bf16(e1 - bf_lo(h1), e1 - bf_lo(h1));
        float c[8];
#pragma unroll
        for (int i = 0; i < 8; i++) c[i] = 0.f;
#pragma unroll
        for (int k2 = 0; k2 < 16; k2++) {
          uint32_t b[4], o[8];
          ldmatrix4(C.sb + SM_WR + (C.lane >> 3) * 16 + k2 * 64, b[0], b[1], b[2], b[3]);
#pragma unroll
          for (int j = 0; j < 8; j++) o[j] = fma_bf16x2(af[8 * k2 + j], (j & 1) ? h1 : h0, mul_bf16x2(af[8 * k2 + j], (j & 1) ? l1 : l0));
          mma_16816(c, o, b[0], b[1]);
          mma_16816(c + 4, o + 4, b[2], b[3]);
        }
        const int row = g * 64 + C.warp * 16 + (C.lane >> 2);
        uint32_t u0 = __float_as_uint(bf16_round(c[0] + c[4]) + 0.0f), u1 = __float_as_uint(bf16_round(c[2] + c[6]) + 0.0f);
        u0 = (u0 & 0x80000000u) ? ~u0 : (u0 | 0x80000000u); u1 = (u1 & 0x80000000u) ? ~u1 : (u1 | 0x80000000u);
        const uint32_t um = __reduce_max_sync(0xffffffffu, max(u0, u1));
        const uint32_t rm = __reduce_min_sync(0xffffffffu, u0 == um ? (uint32_t)row : (u1 == um ? (uint32_t)row + 8u : 0xFFFFFFFFu));
        const unsigned long long key = ((unsigned long long)um << 32) | (unsigned long long)(0xFFFFFFFFu - rm);
        if (C.lane == 0) asm volatile("red.relaxed.gpu.global.max.u64 [%0], %1;" ::"l"(&g_flags.key[C.epoch & 1]), "l"(key) : "memory");
        PROFC(59);
      }
    }
  }
}

__device__ __forceinline__ void proj_spare(Cons& C) {
  uint32_t af[128];
  float acc[64];
  const int mat = C.lane >> 3;
  const uint32_t off = ((mat >> 1) * 8 + (C.lane & 7)) * 128 + (((C.warp * 2 + (mat & 1)) ^ (C.lane & 7)) << 4);
#pragma unroll
  for (int st = 0; st < 2; st++) {
    const uint32_t r = C.w * 16 + st * 8;
    C.wait_full(r);
    const uint32_t base = C.stage_addr(r) + off;
#pragma unroll
    for (int kk = 0; kk < 16; kk++)
      ldmatrix4_t(base + kk * 2048, af[st * 64 + kk * 4], af[st * 64 + kk * 4 + 1], af[st * 64 + kk * 4 + 2], af[st * 64 + kk * 4 + 3]);
    C.release_after<16>(af + st * 64, r, 2);
  }
  C.ring = 32;
#pragma unroll 1
  for (int t = 0; t < 16; t++) {
    uint32_t prev = 0;
    C.turn_sync();
#pragma unroll
    for (int c = 0; c < 4; c++) {
      C.wait_full(C.ring);
      const uint32_t blo = desc_lo(C.stage_addr(C.ring), 16);
      WG_FENCE();
#pragma unroll
      for (int kk = 0; kk < 8; kk++)
        mma_rs128<0>(acc, af[c * 32 + kk * 4], af[c * 32 + kk * 4 + 1], af[c * 32 + kk * 4 + 2], af[c * 32 + kk * 4 + 3],
                     blo + (((kk >> 2) * 16384 + (kk & 3) * 32) >> 4), (c | kk) != 0);
      WG_COMMIT();
      if (c == 3 && t + C.w < 16) C.turn_pass();
      if (c > 0) { WG_WAIT(1); C.release(prev); }
      prev = C.ring;
      C.ring = rnext(C.ring);
    }
    WG_WAIT(0);
    C.release(prev);
    fence_regs(acc);
    mbar_wait(C.bars + B_STFREE + C.w * 8, C.stphase); C.stphase ^= 1;
    const uint32_t base = C.sb + SM_STG + C.w * 16384 + off;
#pragma unroll
    for (int jj = 0; jj < 8; jj++)
      stmatrix4_t(base + jj * 2048, pack_bf16(acc[8 * jj], acc[8 * jj + 1]), pack_bf16(acc[8 * jj + 2], acc[8 * jj + 3]),
                  pack_bf16(acc[8 * jj + 4], acc[8 * jj + 5]), pack_bf16(acc[8 * jj + 6], acc[8 * jj + 7]));
    fence_async_smem();
    bar_arrive(3 + C.w, 160);
    PROFC(t);
  }
}

__device__ __forceinline__ void att_phase(Cons& C, const int a) {
  constexpr int P1 = PP1;
  float o[64];
  uint32_t q[32], p[32];
#pragma unroll
  for (int i = 0; i < 64; i++) o[i] = 0.f;
  fence_regs(o);
#pragma unroll
  for (int i = 0; i < 32; i++) p[i] = 0u;
  const uint32_t qoff = C.frag_off();
  uint32_t kr = C.ring, qr = rnext(kr), vr = 0, ring = rnext(qr);
  C.wait_full(kr);
  const int sw = a + (int)C.rank;
  const int lim = C.warp * 16 + (C.lane >> 2) - 2 * (C.lane & 3);
  float m0 = 0.f, m1 = 0.f, l0 = 1.f, l1 = 1.f, a0 = 1.f, a1 = 1.f, t0, t1;
  bool usem = false, halfpv = false, bad;
  uint32_t ready;
  int st = 0, gs = 0, pvacc = 0;
  auto step = [&](auto kind) {
    constexpr bool FAST = decltype(kind)::value == 0, light = decltype(kind)::value == 2;
    const uint32_t klo = desc_lo(C.stage_addr(kr), 16), vlo = desc_lo(C.stage_addr(vr), 16384);
    const bool first = !FAST && (st == 0 || st == sw);
    const bool diag = !FAST && (light || st == sw - C.w);
    const uint32_t ck = kr, cv = vr, cq = qr;
    const uint32_t qbase = C.stage_addr(qr) + ((C.w ^ (st != 0)) << 14);
    constexpr int N = light ? 8 : 16, PA = N < P1 ? N : P1;
    float s[4 * N];
    auto scores = [&](bool acc) {
      if (first) C.wait_full(qr);
      C.turn_sync();
      if (first) {
        const uint32_t qlo = desc_lo(qbase, 16);
        WG_FENCE();
#pragma unroll
        for (int kk = 0; kk < 8; kk++) qk_ss(s, qlo + (((kk >> 2) * 8192 + (kk & 3) * 32) >> 4), klo + (((kk >> 2) * 16384 + (kk & 3) * 32) >> 4), kk || acc);
        WG_COMMIT();
      } else {
        WG_FENCE();
#pragma unroll
        for (int kk = 0; kk < 8; kk++) qk_rs(s, q + 4 * kk, klo + (((kk >> 2) * 16384 + (kk & 3) * 32) >> 4), kk || acc);
        WG_COMMIT();
      }
    };
    if (diag) {
#pragma unroll
      for (int i = 0; i < 4 * N; i++) {
        const int c = i - (4 * N - 32);
        s[i] = c < 0 ? 0.f : __int_as_float(__viaddmin_s32(lim << 23, -((8 * (c >> 2) + (c & 1) - 8 * ((c >> 1) & 1)) * (1 << 23)), 0));
      }
      fence_regs(s);
      scores(true);
    } else {
      scores(false);
    }
    {
      const bool qn = st == a - 1 || (st == 16 && gs != 33);
      kr = ring;
      const uint32_t r1 = rnext(ring), r2 = rnext(r1);
      qr = qn ? r1 : qr;
      vr = gs == 33 ? ring : (qn ? r2 : r1);
      ring = rnext(vr);
    }
    if (!FAST && !light && halfpv) {
      WG_FENCE();
#pragma unroll
      for (int kk = 0; kk < 4; kk++) mma_rs128<1>(o, p[4 * kk], p[4 * kk + 1], p[4 * kk + 2], p[4 * kk + 3], vlo + kk * 128, kk ? 1 : pvacc);
      WG_COMMIT();
    } else if (FAST || gs > 0) {
      if (!FAST) WG_FENCE();
#pragma unroll
      for (int kk = 0; kk < 8; kk++) mma_rs128<1>(o, p[4 * kk], p[4 * kk + 1], p[4 * kk + 2], p[4 * kk + 3], vlo + kk * 128, kk ? 1 : pvacc);
      WG_COMMIT();
    } else {
      WG_COMMIT();
    }
    C.turn_pass();
    if (!FAST) {
      if (first) {
        const uint32_t base = qbase + qoff;
        const float u0 = __shfl_xor_sync(0xffffffffu, l0, 1), u1 = __shfl_xor_sync(0xffffffffu, l1, 1);
#pragma unroll
        for (int kk = 0; kk < 4; kk++) ldmatrix4(base ^ ((2 * kk) << 4), q[4 * kk], q[4 * kk + 1], q[4 * kk + 2], q[4 * kk + 3]);
        l0 += u0; l1 += u1;
        a0 = __shfl_xor_sync(0xffffffffu, l0, 2); a1 = __shfl_xor_sync(0xffffffffu, l1, 2);
#pragma unroll
        for (int kk = 4; kk < 8; kk++) ldmatrix4((base ^ ((2 * (kk & 3)) << 4)) + 8192, q[4 * kk], q[4 * kk + 1], q[4 * kk + 2], q[4 * kk + 3]);
        a0 = rcp(a0 + l0); a1 = rcp(a1 + l1);
        l0 = 0.f; l1 = 0.f; m0 = 0.f; m1 = 0.f; usem = false;
      }
      halfpv = light;
    }
    WG_WAIT(1);
    fence_regs(s);
    C.release(ck);
    if (first) C.release_after<8>(q, cq);
    if (__builtin_expect(usem, 0)) {
#pragma unroll
      for (int i = 0; i < N; i++) { s[4 * i] -= m0; s[4 * i + 1] -= m0; s[4 * i + 2] -= m1; s[4 * i + 3] -= m1; }
    }
#pragma unroll
    for (int i = 0; i < PA; i++) {
      s[4 * i] = ex2(s[4 * i]); s[4 * i + 1] = ex2(s[4 * i + 1]); s[4 * i + 2] = ex2(s[4 * i + 2]); s[4 * i + 3] = ex2(s[4 * i + 3]);
      if (i == 0) { t0 = s[0] + s[1]; t1 = s[2] + s[3]; }
      else { t0 += s[4 * i] + s[4 * i + 1]; t1 += s[4 * i + 2] + s[4 * i + 3]; }
    }
    if (__builtin_expect(!(t0 + t1 <= 0x1p30f), 0)) C.wait_full(kr);
    WG_WAIT(0);
    fence_regs(o);
    if (FAST || gs > 0) C.release(cv);
    ready = mbar_test2(C.bars + B_FULL + (kr & ~7u), kr & 1u, C.bars + B_FULL + (vr & ~7u), vr & 1u);
#pragma unroll
    for (int i = 0; i < N; i++) {
      if (i >= PA) {
        s[4 * i] = ex2(s[4 * i]); s[4 * i + 1] = ex2(s[4 * i + 1]); s[4 * i + 2] = ex2(s[4 * i + 2]); s[4 * i + 3] = ex2(s[4 * i + 3]);
        t0 += s[4 * i] + s[4 * i + 1]; t1 += s[4 * i + 2] + s[4 * i + 3];
      }
      p[2 * i] = pack_bf16(s[4 * i], s[4 * i + 1]); p[2 * i + 1] = pack_bf16(s[4 * i + 2], s[4 * i + 3]);
    }
    bad = !(t0 <= 0x1p30f && t1 <= 0x1p30f);
    if (first) {
      uint32_t u0 = __ballot_sync(0xffffffffu, t0 >= 0x1p-30f), u1 = __ballot_sync(0xffffffffu, t1 >= 0x1p-30f);
      u0 |= u0 >> 1; u1 |= u1 >> 1; u0 |= u0 >> 2; u1 |= u1 >> 2;
      bad = bad || (~(u0 & u1) & 0x11111111u) != 0u;
      if (gs > 0) C.stage_out(o, a0, a1);
    }
    pvacc = first ? 0 : 1;
  };
  const uint32_t special = 1u | ((C.w ? 7u : 3u) << (sw - 1));
  PROFC(12);
  auto tail = [&]() {
    if (__builtin_expect(__any_sync(0xffffffffu, bad), 0)) {
      const unsigned char* kg = g_kv + (size_t)(((blockIdx.x >> 3) + (gs >= 17 ? 16 : 0)) * 32 + (st < sw ? st : 16 - st)) * 32768;
      const uint32_t koff = (C.lane >> 2) * 144 + (C.lane & 3) * 4;
      const int dlim = (st == sw - 1 || st == sw) ? (halfpv ? lim : lim + 64) : 1024;
      float n0 = -INFINITY, n1 = -INFINITY;
#pragma unroll 1
      for (int it = 0; it < 16; it++) {
        const int jp = it & 7;
        float c[8];
        uint32_t b[32];
#pragma unroll
        for (int i = 0; i < 8; i++) c[i] = 0.f;
#pragma unroll
        for (int i = 0; i < 32; i++)
          b[i] = __ldcg(reinterpret_cast<const uint32_t*>(kg + jp * 2048 + (koff ^ (((i >> 1) & 6) + (i & 1)) << 4) + (i >> 4) * 16384 + (i & 2) * 512));
#pragma unroll
        for (int kk = 0; kk < 8; kk++) {
          mma_16816(c, q + 4 * kk, b[4 * kk], b[4 * kk + 1]);
          mma_16816(c + 4, q + 4 * kk, b[4 * kk + 2], b[4 * kk + 3]);
        }
#pragma unroll
        for (int i = 0; i < 8; i++) if (16 * jp + 8 * (i >> 2) + (i & 1) - 8 * ((i >> 1) & 1) > dlim) c[i] = -INFINITY;
        if (it < 8) {
          n0 = fmaxf(fmaxf(n0, fmaxf(c[0], c[1])), fmaxf(c[4], c[5])); n1 = fmaxf(fmaxf(n1, fmaxf(c[2], c[3])), fmaxf(c[6], c[7]));
          if (it == 7) {
            n0 = fmaxf(n0, __shfl_xor_sync(0xffffffffu, n0, 1)); n1 = fmaxf(n1, __shfl_xor_sync(0xffffffffu, n1, 1));
            n0 = fmaxf(n0, __shfl_xor_sync(0xffffffffu, n0, 2)); n1 = fmaxf(n1, __shfl_xor_sync(0xffffffffu, n1, 2));
            if (pvacc) {
              n0 = fmaxf(n0, m0); n1 = fmaxf(n1, m1);
              const float f0 = ex2(m0 - n0), f1 = ex2(m1 - n1);
              l0 *= f0; l1 *= f1;
#pragma unroll
              for (int i = 0; i < 16; i++) { o[4 * i] *= f0; o[4 * i + 1] *= f0; o[4 * i + 2] *= f1; o[4 * i + 3] *= f1; }
            }
            m0 = n0; m1 = n1; usem = true;
            t0 = 0.f; t1 = 0.f;
          }
        } else {
#pragma unroll
          for (int i = 0; i < 8; i++) c[i] = ex2(c[i] - ((i & 2) ? m1 : m0));
          t0 += (c[0] + c[1]) + (c[4] + c[5]); t1 += (c[2] + c[3]) + (c[6] + c[7]);
#pragma unroll
          for (int i = 0; i < 28; i++) p[i] = p[i + 4];
#pragma unroll
          for (int i = 0; i < 4; i++) p[28 + i] = pack_bf16(c[2 * i], c[2 * i + 1]);
        }
      }
      __syncwarp();
    }
    l0 += t0; l1 += t1;
    st = st == 16 ? 0 : st + 1;
    if (!ready) { C.wait_full(kr); C.wait_full(vr); }
    PROFC(13 + gs);
    gs++;
  };
#pragma unroll 1
  while (gs < 34) {
    if (st == sw - 1 + C.w) { step(std::integral_constant<int, 2>()); tail(); }
    else { step(std::integral_constant<int, 1>()); tail(); }
#pragma unroll 1
    while (!((special >> st) & 1u)) { step(std::integral_constant<int, 0>()); tail(); }
  }
  {
    const uint32_t vlo = desc_lo(C.stage_addr(vr), 16384);
    C.turn_sync();
    if (halfpv) {
      WG_FENCE();
#pragma unroll
      for (int kk = 0; kk < 4; kk++) mma_rs128<1>(o, p[4 * kk], p[4 * kk + 1], p[4 * kk + 2], p[4 * kk + 3], vlo + kk * 128, kk ? 1 : pvacc);
      WG_COMMIT();
    } else {
      WG_FENCE();
#pragma unroll
      for (int kk = 0; kk < 8; kk++) mma_rs128<1>(o, p[4 * kk], p[4 * kk + 1], p[4 * kk + 2], p[4 * kk + 3], vlo + kk * 128, kk ? 1 : pvacc);
      WG_COMMIT();
    }
    if (C.w == 0) C.turn_pass();
    l0 += __shfl_xor_sync(0xffffffffu, l0, 1); l1 += __shfl_xor_sync(0xffffffffu, l1, 1);
    l0 += __shfl_xor_sync(0xffffffffu, l0, 2); l1 += __shfl_xor_sync(0xffffffffu, l1, 2);
    a0 = rcp(l0); a1 = rcp(l1);
    WG_WAIT(0);
    C.release(vr);
    fence_regs(o);
    C.stage_out(o, a0, a1);
    PROFC(47);
  }
  C.ring = ring;
}

__device__ __forceinline__ void op_phase(Cons& C, const Params& P, int pair) {
  const int tile = pair >> 2, ks = pair & 3;
  const int j = tile >> 1, nh = tile & 1;
  float acc[128];
  uint32_t pb = 0;
  const int tid = C.warp * 32 + C.lane;
  const int g = 4 * j + 2 * (int)C.rank + C.w;
  const int kh = 4 * nh + ks;
  const int row0 = g * 64 + C.warp * 16 + (C.lane >> 2);
  uint32_t xv[16], nv[16], st[4], selk;
  {
    const uint32_t* xp = reinterpret_cast<const uint32_t*>(P.x + (size_t)row0 * DM + kh * 64) + (C.lane & 3);
    asm volatile("ld.global.cg.u32 %0, [%1];" : "=r"(selk) : "l"(&g_flags.key[C.epoch & 1]));
    asm volatile("ld.global.cg.v2.u32 {%0,%1}, [%2];" : "=r"(st[0]), "=r"(st[1]) : "l"(g_stat + row0));
    asm volatile("ld.global.cg.v2.u32 {%0,%1}, [%2];" : "=r"(st[2]), "=r"(st[3]) : "l"(g_stat + row0 + 8));
#pragma unroll
    for (int i = 0; i < 16; i++) asm volatile("ld.global.nc.u32 %0, [%1];" : "=r"(xv[i]) : "l"(xp + (i & 1) * 8 * (DM / 2) + (i >> 1) * 4));
  }
  auto head = [&](int t, auto kind) {
    constexpr int KIND = decltype(kind)::value;
    const uint32_t i0 = C.ring, ia = rnext(i0), i1 = rnext(ia);
    C.ring = rnext(i1);
    const uint32_t alo = desc_lo(C.stage_addr(ia) + C.w * 8192, 16);
    C.wait_full(i0);
    const uint32_t b0 = desc_lo(C.stage_addr(i0), 8192);
    if (KIND == 2 && C.w == 1) C.turn_sync();
    WG_FENCE();
#pragma unroll
    for (int kk = 0; kk < 4; kk++) {
      if (KIND == 0) mma_ss256(acc, alo + kk * 2, b0 + kk * 128, kk ? 1 : t);
      else mma_ss192(acc, alo + kk * 2, b0 + kk * 128);
    }
    WG_COMMIT();
    if (t > 0) { WG_WAIT(1); if (KIND < 2) C.release(pb); }
    C.wait_full(i1);
    const uint32_t b1 = desc_lo(C.stage_addr(i1), 8192);
    WG_FENCE();
#pragma unroll
    for (int kk = 0; kk < 4; kk++) {
      if (KIND == 0) mma_ss256(acc, alo + 1024 + kk * 2, b1 + kk * 128, 1);
      else mma_ss192(acc, alo + 1024 + kk * 2, b1 + kk * 128);
    }
    WG_COMMIT();
    if (KIND == 2 && C.w == 0) C.turn_pass();
    if (KIND == 0) { WG_WAIT(1); C.release(i0); }
    pb = i1;
  };
#pragma unroll 1
  for (int t = 0; t < 6; t++) head(t, std::integral_constant<int, 0>());
  uint32_t rd = C.ring;
  head(1, std::integral_constant<int, 1>());
  head(1, std::integral_constant<int, 2>());
  cluster_arrive();
  WG_WAIT(0);
  fence_regs(acc);
  PROFC(48);
  const int sub = (int)C.rank * 2 + C.w;
  const uint32_t tag = ~C.epoch & 1u;
#pragma unroll
  for (int pp = 1; pp < 4; pp++) {
    uint4* dst = g_exch + (size_t)(((tile * 4 + ((pp + ks) & 3)) * 3 + (pp - 1)) * 4 + sub) * 512 + tid;
#pragma unroll
    for (int v = 0; v < 4; v++) {
      const float* f = acc + 32 * (pp - 1) + 8 * v;
      st_relaxed128(dst + v * 128, (pack_bf16(f[0], f[1]) & ~1u) | tag, pack_bf16(f[2], f[3]), pack_bf16(f[4], f[5]), pack_bf16(f[6], f[7]));
    }
  }
  __syncwarp();
  if (C.lane < 3) red_relaxed(&g_flags.ctx[(tile * 4 + ((C.lane + 1 + ks) & 3)) * 4 + sub][4 + C.warp], 1);
  PROFC(49);
  float own[32];
  WG_FENCE();
#pragma unroll
  for (int t = 0; t < 2; t++) {
    const uint32_t ia = rnext(rd), i1 = rnext(ia);
    const uint32_t alo = desc_lo(C.stage_addr(ia) + C.w * 8192, 16), b0 = desc_lo(C.stage_addr(rd), 8192), b1 = desc_lo(C.stage_addr(i1), 8192);
    rd = rnext(i1);
#pragma unroll
    for (int kk = 0; kk < 8; kk++) mma_ss64(own, alo + (kk >> 2) * 1024 + (kk & 3) * 2, (kk < 4 ? b0 : b1) + 1536 + (kk & 3) * 128, t || kk);
  }
  WG_COMMIT();
  {
    const int sel = (int)(0xFFFFFFFFu - selk);
#pragma unroll
    for (int i = 0; i < 16; i++) {
      const uint32_t d = add_bf16x2(xv[i], st[(i & 1) * 2]);
      const float rs = __uint_as_float(st[(i & 1) * 2 + 1]);
      nv[i] = pack_bf16(bf_lo(d) * rs, bf_hi(d) * rs);
    }
    if ((sel >> 4) == g * 4 + C.warp) {
      flag_wait(&g_flags.moe_fin, C.epoch + 1);
      __syncwarp();
      const uint32_t* sp = g_selrow + kh * 32 + (C.lane & 3);
#pragma unroll
      for (int i = 0; i < 16; i++) if (row0 + (i & 1) * 8 == sel) nv[i] = __ldcg(sp + (i >> 1) * 4);
    }
  }
  PROFC(50);
  const uint4* src = g_exch + (size_t)((tile * 4 + ks) * 3 * 4 + sub) * 512 + tid;
  uint4 e[12];
#pragma unroll 1
  for (int it = 0;; it++) {
    uint32_t any = 0, all = 1;
    if (it == 0) {
      if (C.lane == 0) {
        const unsigned* hint = &g_flags.ctx[(tile * 4 + ks) * 4 + sub][4 + C.warp];
        while ((int)(ld_relaxed(hint) - (C.epoch + 1) * 3) < 0) {}
      }
      __syncwarp();
    }
#pragma unroll
    for (int i = 0; i < 12; i++) e[i] = ld_relaxed128(src + (i >> 2) * 2048 + (i & 3) * 128);
#pragma unroll
    for (int i = 0; i < 12; i++) { any |= e[i].x; all &= e[i].x; }
    if (__all_sync(0xffffffffu, ((tag ? all : ~any) & 1u) != 0u)) break;
  }
  PROFC(52);
#pragma unroll
  for (int i = 0; i < 12; i++) {
    float* d = acc + 96 + 8 * (i & 3);
    d[0] += bf_lo(e[i].x); d[1] += bf_hi(e[i].x); d[2] += bf_lo(e[i].y); d[3] += bf_hi(e[i].y);
    d[4] += bf_lo(e[i].z); d[5] += bf_hi(e[i].z); d[6] += bf_lo(e[i].w); d[7] += bf_hi(e[i].w);
  }
  WG_WAIT(0);
  fence_regs(own);
#pragma unroll
  for (int i = 0; i < 32; i++) acc[96 + i] += own[i];
  mbar_wait(C.bars + B_STFREE + C.w * 8, C.stphase);
  const uint32_t stg = C.sb + SM_STG + C.w * 16384;
  {
    const uint32_t base = stg + C.frag_off();
#pragma unroll
    for (int jj = 0; jj < 4; jj++) {
      uint32_t ou[4];
#pragma unroll
      for (int i = 0; i < 4; i++) ou[i] = add_bf16x2(add_bf16x2(xv[4 * jj + i], pack_bf16(acc[96 + 8 * jj + 2 * i], acc[96 + 8 * jj + 2 * i + 1])), nv[4 * jj + i]);
      stmatrix4(base ^ ((2 * jj) << 4), ou[0], ou[1], ou[2], ou[3]);
    }
  }
  __syncwarp();
  PROFC(54);
#pragma unroll
  for (int i = 0; i < 4; i++) {
    const int idx = C.warp * 128 + C.lane + 32 * i, row = idx >> 3, ch = (idx ^ row) & 7;
    uint4 av;
    asm volatile("ld.shared.v4.u32 {%0,%1,%2,%3}, [%4];" : "=r"(av.x), "=r"(av.y), "=r"(av.z), "=r"(av.w) : "r"(stg + idx * 16) : "memory");
    *reinterpret_cast<uint4*>(P.out + (size_t)(g * 64 + row) * DM + kh * 64 + ch * 8) = av;
  }
  PROFC(51);
}

__device__ __forceinline__ void moe_phase(Cons& C, const Params& P, int part, unsigned char* smem) {
  const int tid = C.w * 128 + C.warp * 32 + C.lane;
  float* xs = reinterpret_cast<float*>(smem + SM_STG);
  float* hs = xs + 512;
  float* red = xs + 1024;
  if (tid == 0) flag_wait(&g_flags.ln_done, (C.epoch + 1) * 32);
  mbar_wait(C.bars + B_STFREE + C.w * 8, C.stphase);
  bar_sync(5, 256);
  const unsigned long long key = __ldcg(&g_flags.key[C.epoch & 1]);
  const int sel = (int)(0xFFFFFFFFu - (uint32_t)key);
  {
    const int c2 = tid * 2;
    const uint2 st = __ldcg(g_stat + sel);
    const uint32_t d = add_bf16x2(__ldg(reinterpret_cast<const uint32_t*>(P.x + (size_t)sel * DM) + tid), st.x);
    const uint32_t u = pack_bf16(bf_lo(d) * __uint_as_float(st.y), bf_hi(d) * __uint_as_float(st.y));
    xs[c2] = bf_lo(u); xs[c2 + 1] = bf_hi(u);
  }
  bar_sync(5, 256);
  auto accumulate = [&](float (&a)[8], uint32_t off, uint32_t pitch, const float* v) {
    C.wait_full(C.ring);
    const uint32_t base = C.stage_addr(C.ring) + off;
    uint32_t wv[32];
#pragma unroll
    for (int i = 0; i < 8; i++)
      asm volatile("ld.shared.v4.u32 {%0,%1,%2,%3}, [%4];" : "=r"(wv[4 * i]), "=r"(wv[4 * i + 1]), "=r"(wv[4 * i + 2]), "=r"(wv[4 * i + 3]) : "r"(base + i * pitch) : "memory");
    C.release_after<8>(wv, C.ring);
    C.ring = rnext(C.ring);
#pragma unroll
    for (int i = 0; i < 8; i++) {
      const float f = v[i];
#pragma unroll
      for (int e = 0; e < 4; e++) { a[2 * e] += f * bf_lo(wv[4 * i + e]); a[2 * e + 1] += f * bf_hi(wv[4 * i + e]); }
    }
  };
  {
    const int chunk = tid % 56, kg = (tid / 56) & 3;
    const uint32_t off = (chunk / 28) * 14336 + (chunk % 28) * 16 + kg * 8 * 448;
    float ag[8], au[8];
#pragma unroll
    for (int e = 0; e < 8; e++) { ag[e] = 0.f; au[e] = 0.f; }
#pragma unroll 1
    for (int u = 0; u < 16; u++) { accumulate(ag, off, 448, xs + u * 32 + kg * 8); accumulate(au, off, 448, xs + u * 32 + kg * 8); }
    if (tid < 224) {
#pragma unroll
      for (int e = 0; e < 8; e++) { red[(kg * 2) * 448 + chunk * 8 + e] = ag[e]; red[(kg * 2 + 1) * 448 + chunk * 8 + e] = au[e]; }
    }
  }
  bar_sync(5, 256);
  for (int f = tid; f < 448; f += 256) {
    float gs = 0.f, us = 0.f;
#pragma unroll
    for (int kg = 0; kg < 4; kg++) { gs += red[(kg * 2) * 448 + f]; us += red[(kg * 2 + 1) * 448 + f]; }
    gs = bf16_round(gs); us = bf16_round(us);
    const float sl = bf16_round(gs / (1.0f + expf(-gs)));
    hs[f] = bf16_round(sl * us);
  }
  bar_sync(5, 256);
  {
    const int chunk = tid & 63, rg = tid >> 6;
    float ay[8];
#pragma unroll
    for (int e = 0; e < 8; e++) ay[e] = 0.f;
#pragma unroll 1
    for (int u = 0; u < 14; u++) accumulate(ay, chunk * 16 + rg * 8192, 1024, hs + u * 32 + rg * 8);
#pragma unroll
    for (int e = 0; e < 8; e++) red[rg * 512 + chunk * 8 + e] = ay[e];
  }
  bar_sync(5, 256);
  for (int c = tid; c < DM; c += 256) g_ypart[part * DM + c] = red[c] + red[512 + c] + red[1024 + c] + red[1536 + c];
  bar_sync(5, 256);
  if (tid == 0) red_release(&g_flags.moe_done, 1);
  if (part == 0) {
    if (tid == 0) flag_wait(&g_flags.moe_done, (C.epoch + 1) * 4);
    bar_sync(5, 256);
    uint32_t ub = (uint32_t)(key >> 32);
    ub = (ub & 0x80000000u) ? (ub & 0x7FFFFFFFu) : ~ub;
    const float sig = bf16_round(1.0f / (1.0f + expf(-__uint_as_float(ub))));
    float y0 = 0.f, y1 = 0.f;
#pragma unroll
    for (int c = 0; c < 4; c++) { y0 += __ldcg(&g_ypart[c * DM + 2 * tid]); y1 += __ldcg(&g_ypart[c * DM + 2 * tid + 1]); }
    y0 = bf16_round(bf16_round(y0) * sig); y1 = bf16_round(bf16_round(y1) * sig);
    g_selrow[tid] = pack_bf16(xs[2 * tid] + y0, xs[2 * tid + 1] + y1);
    bar_sync(5, 256);
    if (tid == 0) red_release(&g_flags.moe_fin, 1);
  }
}

__device__ __forceinline__ int proj_tile(int t, int cg) {
  return cg < 5 ? ((t >> 1) * 5 + cg) * 4 + (t & 1) : (3 * t + cg - 5) * 4 + 2;
}
__device__ __forceinline__ const __nv_bfloat16* proj_weight(const Params& P, int tile) {
  return ((tile & 2) ? P.w_q : ((tile & 1) ? P.w_uv : P.w_uk)) + (tile >> 2) * 128;
}

__device__ __forceinline__ void load_rows(const Params& P, uint32_t dst, uint32_t fb, int c) {
  mbar_expect_tx(fb, STAGE);
  for (int i = 0; i < 4; i++)
    tma_load(dst + i * 8192, blockIdx.x >= 80 ? &P.tm_x : &P.tm_ckv, (2 * c + (i & 1)) * 64, ((blockIdx.x & 15) * 2 + (i >> 1)) * 64, fb, H_A);
}

__global__ void __launch_bounds__(384, 1) mega_kernel(const __grid_constant__ Params P) {
  extern __shared__ unsigned char smem_raw[];
  const uint32_t sraw = smem_u32(smem_raw);
  const uint32_t sb = (sraw + 1023u) & ~1023u;
  const uint32_t bars = sb + SM_BAR;
  const int warp_id = __shfl_sync(0xffffffffu, threadIdx.x >> 5, 0);
  const int lane = threadIdx.x & 31;
  uint32_t rank; asm volatile("mov.u32 %0, %%cluster_ctarank;" : "=r"(rank));
  const int pair = blockIdx.x >> 1;
  const bool spare = pair >= 64;
  const int jx = (pair & 3) + (pair & 4);
  const int a = 2 * jx + 1;

  if (threadIdx.x == 96) {
    for (int s = 0; s < NST; s++) { mbar_init(bars + B_FULL + s * 8, 1); mbar_init(bars + B_EMPTY + s * 8, 16); }
    mbar_init(bars + B_STFREE, 1); mbar_init(bars + B_STFREE + 8, 1);
    mbar_init(bars + B_DONE, 11);
    asm volatile("fence.mbarrier_init.release.cluster;" ::: "memory");
  }
  if (threadIdx.x == 96 && !spare) {
    fence_async_smem();
    for (int u = 0; u < (pair >= 40 ? NQ : NK); u++) {
      const uint32_t dst = sb + u * STAGE, fb = bars + B_FULL + u * 8;
      if (pair >= 40 ? u < 4 : !(u & 1)) {
        load_rows(P, dst, fb, pair >= 40 ? u : u >> 1);
      } else {
        mbar_expect_tx(fb, STAGE);
        for (int i = 0; i < 2; i++)
          tma_load(dst + i * 16384, pair >= 40 ? &P.tm_wq : &P.tm_wuk, (proj_tile(0, pair >> 3) >> 2) * 128 + i * 64, (pair >= 40 ? u - 4 : u >> 1) * 128, fb, H_W);
      }
    }
  }
  __syncwarp();
  cluster_arrive();
  cluster_wait();

  if (warp_id < 4) {
    asm volatile("setmaxnreg.dec.sync.aligned.u32 40;");
    if (warp_id == 3) {
      uint32_t ring = 1, fb = 0, epoch = 0;
      auto acquire = [&]() -> uint32_t {
        mbar_park(bars + B_EMPTY + (ring & ~7u), ring & 1u);
        fb = bars + B_FULL + (ring & ~7u);
        const uint32_t dst = sb + ((ring & ~7u) << 12);
        ring = rnext(ring);
        return dst;
      };
      auto flag_all = [&](const unsigned* p, unsigned target) { return __all_sync(0xffffffffu, flag_ok(p, target)); };
      if (spare) {
        const CUtensorMap* tw = rank ? &P.tm_wuv : &P.tm_wuk;
        for (int st = 0; st < 4; st++) {
          const uint32_t dst = acquire();
          if (elect_one()) {
            mbar_expect_tx(fb, STAGE);
            for (int i = 0; i < 2; i++) tma_load(dst + i * 16384, tw, (pair - 34) * 128 + (st >> 1) * 64, ((st & 1) * 2 + i) * 128, fb, H_W);
          }
        }
#pragma unroll 1
        for (int u = 0; u < 64; u++) {
          const uint32_t dst = acquire() + rank * 16384;
          if (elect_one()) {
            mbar_expect_tx(fb, STAGE);
            for (int i = 0; i < 2; i++) tma_load_mc(dst + i * 8192, &P.tm_ckv, (u & 3) * 128 + rank * 64, (u >> 2) * 128 + i * 64, fb, EV_NORMAL);
          }
        }
        if (blockIdx.x == 128 && lane == 0) g_flags.key[(read_epoch() + 1) & 1] = 0;
        const int part = (pair - 64) * 2 + (int)rank;
#pragma unroll 1
        for (int u = 0; u < 32; u++) {
          const uint32_t dst = acquire();
          if (elect_one()) {
            mbar_expect_tx(fb, 28672);
            for (int i = 0; i < 2; i++) tma_load(dst + i * 14336, (u & 1) ? &P.tm_wu : &P.tm_wg, part * 448 + i * 224, (u >> 1) * 32, fb, EV_FIRST);
          }
        }
#pragma unroll 1
        for (int u = 0; u < 14; u++) {
          const uint32_t dst = acquire();
          if (elect_one()) {
            mbar_expect_tx(fb, STAGE);
            bulk_load(dst, P.w_down + (size_t)(part * 448 + u * 32) * DM, 32768, fb, EV_FIRST);
          }
        }
      } else {
        PROFP(0);
        const int cg = pair >> 3;
        ring = cg < 5 ? (NK == 6 ? 0 : NK * 8 + 1) : (NQ == 6 ? 0 : NQ * 8 + 1);
        const int h0 = pair >> 2;
        auto head_ready = [&](int h) {
          return flag_all(lane == 0 ? &g_flags.kv_done[h] : (lane == 1 ? &g_flags.q_done[h] : &g_flags.ln_done), (epoch + 1) * (lane == 0 ? 64 : 32));
        };
        bool ready = false;
        const int nt = proj_tiles(cg);
#pragma unroll 1
        for (int t = 0; t < nt; t++) {
          const int tile = proj_tile(t, cg);
          const CUtensorMap* tw = (tile & 2) ? &P.tm_wq : ((tile & 1) ? &P.tm_wuv : &P.tm_wuk);
          for (int c = t ? 0 : (cg < 5 ? NK / 2 : NQ - 4); c < 4; c++) {
            if (t == 0 && cg < 5 && 2 * c >= NK) {
              const uint32_t dst = acquire();
              if (elect_one()) load_rows(P, dst, fb, c);
            }
            const uint32_t dst = acquire();
            if (elect_one()) {
              mbar_expect_tx(fb, STAGE);
              tma_load_mc(dst + rank * 16384, tw, (tile >> 2) * 128 + rank * 64, c * 128, fb, H_W);
            }
          }
          PROFP(24 + t + 12 - nt);
          if (t == nt - 3) { epoch = lds32(bars + B_EPOCH); ready = head_ready(h0); PROFP(36); }
        }
        while (!ready) { ready = head_ready(h0); if (!ready) __nanosleep(40); }
        fence_async_global();
        PROFP(2);
        const unsigned char* kb = g_kv + (size_t)h0 * 2 * 16 * 32768;
        auto kv_load = [&](const unsigned char* base, int s) {
          const uint32_t dst = acquire();
          if (elect_one()) {
            mbar_expect_tx(fb, STAGE);
            if (s == a) bulk_load(dst, base + (size_t)(rank ? a : 16 - a) * 32768, 32768, fb, H_KV);
            else bulk_load_mc(dst + rank * 16384, base + (size_t)(s < a ? s : 16 - s) * 32768 + rank * 16384, 16384, fb, H_KV);
          }
        };
        const int j = pair >> 3, nh = (pair >> 2) & 1, ks = pair & 3;
        auto op_head = [&](int t) { return t < 4 ? ks * 4 + t : 16 + 4 * ks + 2 * (t & 1) + (((j >> 2) ^ (t >> 1)) & 1); };
        int known = 0;
        auto poll = [&]() {
          const bool ok = lane >= 8 || flag_ok(&g_flags.ctx[j * 32 + op_head(lane & 7)][0], (epoch + 1) * 4);
          const unsigned miss = ~__ballot_sync(0xffffffffu, ok);
          known = miss ? __ffs(miss) - 1 : 32;
          __syncwarp();
          fence_async_global();
        };
#pragma unroll 1
        for (int rd = 0; rd < 2; rd++) {
          const int h = h0 + 16 * rd;
          const unsigned char* vb = kb + 16 * 32768;
#pragma unroll 1
          for (int s = 0; s < 17; s++) {
            kv_load(kb, s);
            if (s == 0 || s == a) {
              const int g = s == 0 ? 4 * jx + 2 * (int)rank : 4 * (7 - jx) + 2 - 2 * (int)rank;
              const uint32_t dst = acquire();
              if (elect_one()) {
                mbar_expect_tx(fb, STAGE);
                bulk_load(dst, g_qc + ((size_t)g * 32 + h) * 16384, 16384, fb, H_Q);
                bulk_load(dst + 16384, g_qc + ((size_t)g * 32 + 32 + h) * 16384, 16384, fb, H_Q);
              }
            }
            if (s) kv_load(vb, s - 1);
            else if (rd) kv_load(vb - (size_t)16 * 2 * 16 * 32768, 16);
            if (s >= 12 && ready) {
              ready = !head_ready(h0 + 16);
              while (s == 16 && ready) { __nanosleep(40); ready = !head_ready(h0 + 16); }
              fence_async_global();
              PROFP(3);
            }
          }
          if (rd) kv_load(vb, 16);
          kb += (size_t)16 * 2 * 16 * 32768;
        }
#pragma unroll 1
        for (int t = 0; t < 8; t++) {
          if (known < t + 3) poll();
          while (known <= t) { __nanosleep(60); poll(); }
          PROFP(4 + t);
          const int hh = op_head(t);
          const unsigned char* src = g_qc + ((size_t)(4 * j + 2 * rank) * 32 + hh) * 16384;
          const uint32_t ia = rnext(ring), adst = sb + ((ia & ~7u) << 12);
          if (t < 2) mbar_park(bars + B_EMPTY + (ia & ~7u), ia & 1u);
          for (int bb = 0; bb < 2; bb++) {
            const uint32_t dst = acquire();
            if (bb == 0) ring = rnext(ring);
            if (elect_one()) {
              mbar_expect_tx(fb, STAGE + 16384);
              bulk_load(adst + bb * 16384, src + bb * 8192, 8192, fb, H_OP);
              bulk_load(adst + bb * 16384 + 8192, src + (size_t)32 * 16384 + bb * 8192, 8192, fb, H_OP);
              tma_load_mc(dst + rank * 16384, &P.tm_wo, nh * 256 + ((2 * rank + 1 + ks) & 3) * 64, hh * 128 + bb * 64, fb, H_OP);
              tma_load_mc(dst + rank * 16384 + 8192, &P.tm_wo, nh * 256 + ((2 * rank + 2 + ks) & 3) * 64, hh * 128 + bb * 64, fb, H_OP);
            }
          }
        }
      }
      __syncwarp();
      if (lane == 0) mbar_arrive(bars + B_DONE);
    } else if (warp_id < 2) {
      const int w = warp_id;
      const uint32_t stg = sb + SM_STG + w * 16384;
      if (lane == 0) asm volatile("st.shared.u32 [%0], %1;" ::"r"(bars + B_EPOCH + w * 4), "r"(read_epoch()) : "memory");
      {
        const int cg = pair >> 3, rb = (pair & 7) * 2 + (int)rank;
#pragma unroll 1
        for (int t = spare ? 0 : 12 - proj_tiles(cg); t < 16; t++) {
          unsigned char* dst;
          unsigned* flag;
          uint32_t half = 8192;
          uint64_t pol = EV_NORMAL;
          if (spare) {
            dst = g_kv + ((size_t)((pair - 34) * 2 + rank) * 16 + t) * 32768 + w * 16384;
            flag = &g_flags.kv_done[pair - 34];
          } else if (t < 12) {
            const int tile = proj_tile(t - 12 + proj_tiles(cg), cg), h = tile >> 2;
            if (h >= 16) pol = H_S1;
            if (tile & 2) {
              dst = g_qc + ((size_t)(rb * 2 + w) * 32 + h) * 16384;
              flag = &g_flags.q_done[h];
            } else {
              dst = g_kv + ((size_t)(h * 2 + (tile & 1)) * 16 + rb) * 32768 + w * 8192; half = 16384;
              flag = &g_flags.kv_done[h];
            }
          } else {
            const int h = (pair >> 2) + 16 * ((t >> 1) & 1), y = t & 1;
            const int jj = y ? 7 - jx : jx;
            const int g = 4 * jj + 2 * (y ^ (int)rank) + (w ^ y);
            dst = g_qc + ((size_t)g * 32 + h) * 16384;
            flag = &g_flags.ctx[jj * 32 + h][0];
          }
          bar_sync(3 + w, 160);
          if (lane == 0) {
            bulk_store(dst, stg, 8192, pol);
            bulk_store(dst + half, stg + 8192, 8192, pol);
            bulk_commit();
            bulk_wait_read0();
            mbar_arrive(bars + B_STFREE + w * 8);
            bulk_wait0();
            fence_gpu();
            red_relaxed(flag, 1);
            if (t == 4 && cg == 7) red_relaxed(&g_flags.ln_done, 1);
          }
          __syncwarp();
          if (t == 14 && !spare) l2_prefetch(P.w_o + (size_t)(blockIdx.x * 64 + w * 32 + lane) * 256, 512);
        }
      }
      if (lane == 0) mbar_arrive(bars + B_DONE);
    } else {
      if (!spare) {
        const int cg = pair >> 3, rb = (pair & 7) * 2 + (int)rank;
        const uint32_t c0 = clk32();
        if (lane < 24) touch256(proj_weight(P, proj_tile(0, cg)) + (size_t)(128 + (lane >> 3) * 128 + rb * 8 + (lane & 7)) * 4096);
#pragma unroll 1
        for (int t = 1; t < proj_tiles(cg); t++) {
          while (clk32() - c0 < (uint32_t)(t < 2 ? PF_B : (t - 2) * PF_PER + PF_NS)) __nanosleep(100);
          if (t < PF_T) touch256(proj_weight(P, proj_tile(t, cg)) + (size_t)(rb * 32 + lane) * 4096);
          else l2_prefetch(proj_weight(P, proj_tile(t, cg)) + (size_t)(rb * 32 + lane) * 4096, 256, H_PF);
        }
      }
      if (lane == 0) {
        uint32_t t0 = clk32();
        while (!mbar_try(bars + B_DONE, 0)) { if (clk32() - t0 > TIMEOUT_CLKS) __trap(); }
        red_relaxed(&g_flags.exit_cnt, 1);
      }
      __syncwarp();
    }
    cluster_arrive();
    cluster_wait();
  } else {
    asm volatile("setmaxnreg.inc.sync.aligned.u32 232;");
    Cons C;
    C.sb = sb; C.bars = bars; C.w = (warp_id - 4) >> 2; C.warp = warp_id & 3; C.lane = lane; C.rank = rank;
    C.ring = 0; C.stphase = 1; C.epoch = 0; C.zero = P.zero;
    C.ebase = mapa(bars + B_EMPTY, lane & 1);
    if (lane >= 2) C.ebase = 0;
    asm volatile("" : "+r"(C.ebase));
    PROFC(62);
    if (C.w == 1) bar_arrive(1, 256);
    if (spare) {
      proj_spare(C);
      C.epoch = lds32(bars + B_EPOCH + C.w * 4);
      moe_phase(C, P, (pair - 64) * 2 + (int)rank, smem_raw + (sb - sraw));
      cluster_arrive();
    } else {
      proj_phase(C, P, pair >> 3, ((pair & 7) * 2 + (int)rank) * 2 + C.w);
      att_phase(C, a);
      op_phase(C, P, pair);
    }
    __syncwarp();
    if (lane == 0) mbar_arrive(bars + B_DONE);
    cluster_wait();
  }
}

typedef CUresult (*EncodeFn)(CUtensorMap*, CUtensorMapDataType, cuuint32_t, void*, const cuuint64_t*, const cuuint64_t*, const cuuint32_t*,
                             const cuuint32_t*, CUtensorMapInterleave, CUtensorMapSwizzle, CUtensorMapL2promotion, CUtensorMapFloatOOBfill);

void make_map(EncodeFn enc, CUtensorMap* tm, const void* ptr, int cols, int rows, int box_rows, int box_cols = 64) {
  cuuint64_t dims[2] = {(cuuint64_t)cols, (cuuint64_t)rows};
  cuuint64_t strides[1] = {(cuuint64_t)cols * 2};
  cuuint32_t box[2] = {(cuuint32_t)box_cols, (cuuint32_t)box_rows};
  cuuint32_t es[2] = {1, 1};
  enc(tm, CU_TENSOR_MAP_DATA_TYPE_BFLOAT16, 2, const_cast<void*>(ptr), dims, strides, box, es, CU_TENSOR_MAP_INTERLEAVE_NONE,
      box_cols == 64 ? CU_TENSOR_MAP_SWIZZLE_128B : CU_TENSOR_MAP_SWIZZLE_NONE, CU_TENSOR_MAP_L2_PROMOTION_L2_256B, CU_TENSOR_MAP_FLOAT_OOB_FILL_NONE);
}

}

extern "C" void kernel_launch(void* const* d_in, const int* in_sizes, int n_in, void* d_out, int out_size) {
  (void)in_sizes; (void)n_in; (void)out_size;
  static EncodeFn enc = nullptr;
  if (!enc) {
    void* fn = nullptr;
    cudaDriverEntryPointQueryResult qr;
    cudaGetDriverEntryPoint("cuTensorMapEncodeTiled", &fn, cudaEnableDefault, &qr);
    enc = (EncodeFn)fn;
    cudaFuncSetAttribute(mega_kernel, cudaFuncAttributeMaxDynamicSharedMemorySize, SMEM_BYTES);
  }
  Params P;
  make_map(enc, &P.tm_x, d_in[0], 512, 2048, 64);
  make_map(enc, &P.tm_ckv, d_in[1], 512, 2048, 64);
  make_map(enc, &P.tm_wq, d_in[2], 4096, 512, 128);
  make_map(enc, &P.tm_wuk, d_in[3], 4096, 512, 128);
  make_map(enc, &P.tm_wuv, d_in[4], 4096, 512, 128);
  make_map(enc, &P.tm_wo, d_in[5], 512, 4096, 64);
  make_map(enc, &P.tm_wg, d_in[8], FF, 512, 32, 224);
  make_map(enc, &P.tm_wu, d_in[9], FF, 512, 32, 224);
  P.x = (const __nv_bfloat16*)d_in[0];
  P.ckv = (const __nv_bfloat16*)d_in[1];
  P.w_q = (const __nv_bfloat16*)d_in[2];
  P.w_uk = (const __nv_bfloat16*)d_in[3];
  P.w_uv = (const __nv_bfloat16*)d_in[4];
  P.w_o = (const __nv_bfloat16*)d_in[5];
  P.w_r = (const __nv_bfloat16*)d_in[7];
  P.w_down = (const __nv_bfloat16*)d_in[10];
  P.out = (__nv_bfloat16*)d_out;
  P.zero = 0;
  cudaLaunchConfig_t cfg = {};
  cfg.gridDim = dim3(NCTA); cfg.blockDim = dim3(384); cfg.dynamicSmemBytes = SMEM_BYTES; cfg.stream = cudaStreamPerThread;
  cudaLaunchAttribute at[1];
  at[0].id = cudaLaunchAttributeClusterDimension; at[0].val.clusterDim.x = 2; at[0].val.clusterDim.y = 1; at[0].val.clusterDim.z = 1;
  cfg.attrs = at; cfg.numAttrs = 1;
  cudaLaunchKernelEx(&cfg, mega_kernel, P);
}
```
